```python
import torch

def _softmax(x, axis=-1):
    return torch.softmax(x, dim=axis)
def _gelu(x):
    return torch.nn.functional.gelu(x, approximate="tanh")
def _silu(x):
    return torch.nn.functional.silu(x)
def _sigmoid(x):
    return torch.sigmoid(x)
def _layernorm(x, axis=-1, eps=1e-5):
    m = x.mean(dim=axis, keepdim=True)
    v = x.var(dim=axis, keepdim=True, unbiased=False)
    return (x - m) / torch.sqrt(v + eps)
def _scatter_add(tgt, idx, src, axis=0):
    return tgt.clone().index_add_(axis, idx, src)
def _segment_sum(src, seg, n):
    out = torch.zeros((n,) + src.shape[1:], dtype=src.dtype)
    return out.index_add_(0, seg, src)
def _pad(x, pw):
    flat = tuple(v for pair in reversed(pw) for v in pair)
    return torch.nn.functional.pad(x, flat)

kernel_name = 'interleave_layers__gqa_block_cached__mixer_channel_mlp__decode'

def setup_inputs():

    _w = (lambda a: (lambda t: t.to(torch.bfloat16) if t.is_floating_point() else t)(torch.as_tensor(a)))
    def _A_setup():
        B, Sq, D = 1, 1, 640
        Hq, Hkv, Sk, Dh = 32, 32, 4096, 128
        assert Hq % Hkv == 0, (Hq, Hkv)
        return {
            "x": _w((lambda *s: torch.randn(*s, dtype=torch.bfloat16) * 0.05)(B, Sq, D)),
            "k_cache": _w((lambda *s: torch.randn(*s, dtype=torch.bfloat16) * 3.2)(B, Hkv, Sk, Dh)),
            "v_cache": _w((lambda *s: torch.randn(*s, dtype=torch.bfloat16) * 0.4)(B, Hkv, Sk, Dh)),
            "wq": _w((lambda *s: torch.randn(*s, dtype=torch.bfloat16) * 3.2)(D, Hq * Dh) * (D ** -0.5)),
            "wo": _w((lambda *s: torch.randn(*s, dtype=torch.bfloat16) * 0.4)(Hq * Dh, D) * ((Hq * Dh) ** -0.5)),
        }
    _A_in = _A_setup()

    def _B_setup():
        B, S, D, F = 1, 1, 640, 1728
        return {
            "x": _w((lambda *s: torch.randn(*s, dtype=torch.bfloat16) * 0.05)(B, S, D)),
            "w1": _w((lambda *s: torch.randn(*s, dtype=torch.bfloat16) * 0.4)(D, F) * (D ** -0.5)),
            "b1": _w((lambda *s: torch.randn(*s, dtype=torch.bfloat16) * 0.4)(F)),
            "w2": _w((lambda *s: torch.randn(*s, dtype=torch.bfloat16) * 0.4)(F, D) * (F ** -0.5)),
            "b2": _w((lambda *s: torch.randn(*s, dtype=torch.bfloat16) * 0.2)(D)),
        }
    _B_in = _B_setup()

    return {
        "A_x": _A_in["x"],
        "A_k_cache": _A_in["k_cache"],
        "A_v_cache": _A_in["v_cache"],
        "A_wq": _A_in["wq"],
        "A_wo": _A_in["wo"],
        "B_x": _B_in["x"],
        "B_w1": _B_in["w1"],
        "B_b1": _B_in["b1"],
        "B_w2": _B_in["w2"],
        "B_b2": _B_in["b2"],
    }

def reference(A_x, A_k_cache, A_v_cache, A_wq, A_wo, B_x, B_w1, B_b1, B_w2, B_b2):
    def _A_ref(x, k_cache, v_cache, wq, wo):
        B, Sq, D = x.shape
        Hq, Dh = 32, 128
        Hkv = k_cache.shape[1]
        rep = Hq // Hkv
        q = (lambda x, *d: x.permute(*d))((x @ wq).reshape(B, Sq, Hq, Dh), 0, 2, 1, 3)
        k = (lambda x, n, axis: torch.repeat_interleave(x, n, dim=axis))(k_cache, rep, axis=1)
        v = (lambda x, n, axis: torch.repeat_interleave(x, n, dim=axis))(v_cache, rep, axis=1)
        scores = torch.einsum("bhqd,bhkd->bhqk", q, k) * (Dh ** -0.5)
        p = _softmax(scores, axis=-1)
        o = torch.einsum("bhqk,bhkd->bhqd", p, v)
        return (lambda x, *d: x.permute(*d))(o, 0, 2, 1, 3).reshape(B, Sq, Hq * Dh) @ wo

    def _B_ref(x, w1, b1, w2, b2):
        y = _layernorm(x, axis=-1)
        h = _gelu(torch.einsum("bsd,df->bsf", y, w1) + b1)
        return torch.einsum("bsf,fd->bsd", h, w2) + b2

    x = A_x
    x = x + _A_ref(_layernorm(x, axis=-1), A_k_cache, A_v_cache, A_wq, A_wo)
    x = x + _B_ref(_layernorm(x, axis=-1), B_w1, B_b1, B_w2, B_b2)
    x = x + _A_ref(_layernorm(x, axis=-1), A_k_cache, A_v_cache, A_wq, A_wo)
    x = x + _B_ref(_layernorm(x, axis=-1), B_w1, B_b1, B_w2, B_b2)
    return x
```

```cpp
#include <cuda_runtime.h>
#include <cuda_bf16.h>
#include <stdint.h>

typedef __nv_bfloat16 bf16;

namespace {

constexpr int D_MODEL = 640;
constexpr int NHEAD = 32;
constexpr int SEQ = 4096;
constexpr int DH = 128;
constexpr int FF = 1728;
constexpr int NCTA = 128;
constexpr int NT = 256;
constexpr int KREG_TILES = 5;
constexpr int KSM_TILES = 3;
constexpr int MLP_UNITS = 16;
constexpr int MLP_CTAS = FF / MLP_UNITS;

constexpr int OFF_STAGE = 0;
constexpr int OFF_W2 = 81920;
constexpr int OFF_W1 = OFF_W2 + 20480;
constexpr int OFF_K = OFF_W1 + 20480;
constexpr int OFF_XS = OFF_K + 98304;
constexpr int OFF_XN = OFF_XS + 2560;
constexpr int OFF_WARP = OFF_XN + 2560;
constexpr int OFF_Q = OFF_WARP + 4096;
constexpr int OFF_OEX = OFF_Q + 256;
constexpr int OFF_STAT = OFF_OEX + 512;
constexpr int OFF_HS = OFF_STAT + 128;
constexpr int OFF_BAR = OFF_HS + 64;
constexpr int SMEM_BYTES = OFF_BAR + 64;

constexpr unsigned SPIN_LIMIT = 1u << 24;

__device__ unsigned int g_ctr;
__device__ float g_acc[4][D_MODEL];
__device__ float2 g_ml[2][NCTA];
__device__ unsigned int g_flag[2][NCTA];

struct Params {
    const bf16* x; const bf16* kc; const bf16* vc; const bf16* wq; const bf16* wo;
    const bf16* w1; const bf16* b1; const bf16* w2; const bf16* b2; bf16* out;
};

__device__ __forceinline__ float bf16r(float x) { return __bfloat162float(__float2bfloat16_rn(x)); }
__device__ __forceinline__ float bflo(uint32_t u) { return __uint_as_float(u << 16); }
__device__ __forceinline__ float bfhi(uint32_t u) { return __uint_as_float(u & 0xffff0000u); }

__device__ __forceinline__ uint32_t smem_u32(const void* p) { return (uint32_t)__cvta_generic_to_shared(p); }

__device__ __forceinline__ void mbar_init(uint32_t bar, uint32_t cnt) {
    asm volatile("mbarrier.init.shared::cta.b64 [%0], %1;" :: "r"(bar), "r"(cnt) : "memory");
}
__device__ __forceinline__ void mbar_expect_tx(uint32_t bar, uint32_t bytes) {
    asm volatile("mbarrier.arrive.expect_tx.shared::cta.b64 _, [%0], %1;" :: "r"(bar), "r"(bytes) : "memory");
}
__device__ __forceinline__ void mbar_wait(uint32_t bar, uint32_t parity) {
    unsigned it = 0;
    while (true) {
        uint32_t ok;
        asm volatile("{\n\t.reg .pred p;\n\tmbarrier.try_wait.parity.shared::cta.b64 p, [%1], %2;\n\tselp.u32 %0, 1, 0, p;\n\t}"
                     : "=r"(ok) : "r"(bar), "r"(parity) : "memory");
        if (ok) break;
        if (++it > SPIN_LIMIT) __trap();
    }
}
__device__ __forceinline__ void bulk_g2s(uint32_t dst, const void* src, uint32_t bytes, uint32_t bar) {
    asm volatile("cp.async.bulk.shared::cluster.global.mbarrier::complete_tx::bytes [%0], [%1], %2, [%3];"
                 :: "r"(dst), "l"(src), "r"(bytes), "r"(bar) : "memory");
}
__device__ __forceinline__ void bulk_g2s_hint(uint32_t dst, const void* src, uint32_t bytes, uint32_t bar, uint64_t pol) {
    asm volatile("cp.async.bulk.shared::cluster.global.mbarrier::complete_tx::bytes.L2::cache_hint [%0], [%1], %2, [%3], %4;"
                 :: "r"(dst), "l"(src), "r"(bytes), "r"(bar), "l"(pol) : "memory");
}
__device__ __forceinline__ void bulk_prefetch_l2(const void* src, uint32_t bytes) {
    asm volatile("cp.async.bulk.prefetch.L2.global [%0], %1;" :: "l"(src), "r"(bytes) : "memory");
}
__device__ __forceinline__ void cp_async16_hint(uint32_t dst, const void* src, uint64_t pol) {
    asm volatile("cp.async.cg.shared.global.L2::cache_hint [%0], [%1], 16, %2;" :: "r"(dst), "l"(src), "l"(pol) : "memory");
}
__device__ __forceinline__ void cp_async_wait_all() { asm volatile("cp.async.wait_all;" ::: "memory"); }

__device__ __forceinline__ void ldg128_hint(uint32_t (&r)[4], const void* p, uint64_t pol) {
    asm volatile("ld.global.nc.L1::no_allocate.L2::cache_hint.v4.u32 {%0,%1,%2,%3}, [%4], %5;"
                 : "=r"(r[0]), "=r"(r[1]), "=r"(r[2]), "=r"(r[3]) : "l"(p), "l"(pol));
}
__device__ __forceinline__ void ldg128(uint32_t (&r)[4], const void* p) {
    asm volatile("ld.global.nc.L1::no_allocate.v4.u32 {%0,%1,%2,%3}, [%4];"
                 : "=r"(r[0]), "=r"(r[1]), "=r"(r[2]), "=r"(r[3]) : "l"(p));
}
__device__ __forceinline__ void mma16816(float (&c)[4], uint32_t a0, uint32_t a1, uint32_t a2, uint32_t a3,
                                         uint32_t b0, uint32_t b1) {
    asm volatile("mma.sync.aligned.m16n8k16.row.col.f32.bf16.bf16.f32 {%0,%1,%2,%3}, {%4,%5,%6,%7}, {%8,%9}, {%0,%1,%2,%3};"
                 : "+f"(c[0]), "+f"(c[1]), "+f"(c[2]), "+f"(c[3])
                 : "r"(a0), "r"(a1), "r"(a2), "r"(a3), "r"(b0), "r"(b1));
}
__device__ __forceinline__ void ldmatrix4(uint32_t (&r)[4], uint32_t addr) {
    asm volatile("ldmatrix.sync.aligned.m8n8.x4.shared.b16 {%0,%1,%2,%3}, [%4];"
                 : "=r"(r[0]), "=r"(r[1]), "=r"(r[2]), "=r"(r[3]) : "r"(addr) : "memory");
}
__device__ __forceinline__ void red_add_v4(float* p, float a, float b, float c, float d) {
    asm volatile("red.global.add.v4.f32 [%0], {%1,%2,%3,%4};" :: "l"(p), "f"(a), "f"(b), "f"(c), "f"(d) : "memory");
}
__device__ __forceinline__ unsigned ld_acquire(const unsigned* p) {
    unsigned v; asm volatile("ld.acquire.gpu.global.u32 %0, [%1];" : "=r"(v) : "l"(p) : "memory"); return v;
}
__device__ __forceinline__ void st_release(unsigned* p, unsigned v) {
    asm volatile("st.release.gpu.global.u32 [%0], %1;" :: "l"(p), "r"(v) : "memory");
}
__device__ __forceinline__ void cluster_sync_all() {
    asm volatile("barrier.cluster.arrive.release.aligned;\n\tbarrier.cluster.wait.acquire.aligned;" ::: "memory");
}
__device__ __forceinline__ uint32_t mapa(uint32_t addr, uint32_t rank) {
    uint32_t r; asm volatile("mapa.shared::cluster.u32 %0, %1, %2;" : "=r"(r) : "r"(addr), "r"(rank)); return r;
}
__device__ __forceinline__ void st_cluster_f32(uint32_t addr, float v) {
    asm volatile("st.shared::cluster.f32 [%0], %1;" :: "r"(addr), "f"(v) : "memory");
}
__device__ __forceinline__ void st_cluster_u16(uint32_t addr, uint16_t v) {
    asm volatile("st.shared::cluster.u16 [%0], %1;" :: "r"(addr), "h"(v) : "memory");
}
__device__ __forceinline__ float warp_sum(float v) {
#pragma unroll
    for (int o = 16; o > 0; o >>= 1) v += __shfl_xor_sync(0xffffffffu, v, o);
    return v;
}

__device__ __forceinline__ void ln20(float (&v)[20]) {
    float s = 0.f;
#pragma unroll
    for (int i = 0; i < 20; i++) s += v[i];
    s = warp_sum(s);
    const float mean = s * (1.0f / D_MODEL);
    float ss = 0.f;
#pragma unroll
    for (int i = 0; i < 20; i++) { float d = v[i] - mean; ss += d * d; }
    ss = warp_sum(ss);
    const float var = ss * (1.0f / D_MODEL);
    const float mb = bf16r(mean), vb = bf16r(var);
    const float den = bf16r(sqrtf(bf16r(vb + 1e-5f)));
#pragma unroll
    for (int i = 0; i < 20; i++) v[i] = bf16r(__fdiv_rn(bf16r(v[i] - mb), den));
}

__device__ __forceinline__ void grid_barrier(unsigned target) {
    __syncthreads();
    if (threadIdx.x == 0) {
        __threadfence();
        atomicAdd(&g_ctr, 1u);
        unsigned it = 0;
        while ((int)(ld_acquire(&g_ctr) - target) < 0) { if (++it > SPIN_LIMIT) __trap(); }
    }
    __syncthreads();
}

template <int PASS>
__device__ __forceinline__ void layer_pair(const Params& P, unsigned char* sm, uint32_t (&kreg)[KREG_TILES][2][4][4],
                                           unsigned epoch, uint64_t pol_first) {
    const int tid = threadIdx.x, lane = tid & 31, w = tid >> 5;
    const int g = lane >> 2, t = lane & 3;
    const int b = blockIdx.x, h = b >> 2, c = b & 3, r = b & 1;
    const uint32_t sbase = smem_u32(sm);
    const uint32_t bar_stage = sbase + OFF_BAR;
    bf16* xs_cur = reinterpret_cast<bf16*>(sm + OFF_XS) + (PASS == 0 ? 0 : D_MODEL);
    bf16* xs_mid = reinterpret_cast<bf16*>(sm + OFF_XS) + (PASS == 0 ? D_MODEL : 0);
    float* xn = reinterpret_cast<float*>(sm + OFF_XN);
    float* wscr = reinterpret_cast<float*>(sm + OFF_WARP);
    bf16* qs = reinterpret_cast<bf16*>(sm + OFF_Q);
    float* oex = reinterpret_cast<float*>(sm + OFF_OEX);
    float* stat = reinterpret_cast<float*>(sm + OFF_STAT);
    float* hs = reinterpret_cast<float*>(sm + OFF_HS);
    const unsigned base = epoch << 9;

    {
        float v[20];
#pragma unroll
        for (int i = 0; i < 20; i++) v[i] = __bfloat162float(xs_cur[lane + 32 * i]);
        ln20(v);
        if (w == 0) {
#pragma unroll
            for (int i = 0; i < 20; i++) xn[lane + 32 * i] = v[i];
        }
    }
    __syncthreads();

    mbar_wait(bar_stage, 0);
    {
        const int cc = tid & 7, rg = tid >> 3;
        float a[8];
#pragma unroll
        for (int i = 0; i < 8; i++) a[i] = 0.f;
#pragma unroll 5
        for (int j = 0; j < 20; j++) {
            const int row = rg + 32 * j;
            const uint4 wv = *reinterpret_cast<const uint4*>(sm + OFF_STAGE + row * 128 + cc * 16);
            const float xv = xn[row];
            a[0] += xv * bflo(wv.x); a[1] += xv * bfhi(wv.x);
            a[2] += xv * bflo(wv.y); a[3] += xv * bfhi(wv.y);
            a[4] += xv * bflo(wv.z); a[5] += xv * bfhi(wv.z);
            a[6] += xv * bflo(wv.w); a[7] += xv * bfhi(wv.w);
        }
#pragma unroll
        for (int i = 0; i < 8; i++) {
            a[i] += __shfl_xor_sync(0xffffffffu, a[i], 8);
            a[i] += __shfl_xor_sync(0xffffffffu, a[i], 16);
        }
        if (lane < 8) {
#pragma unroll
            for (int i = 0; i < 8; i++) wscr[w * 64 + cc * 8 + i] = a[i];
        }
    }
    __syncthreads();
    if (tid == 0) {
        mbar_expect_tx(bar_stage, 81920);
        const bf16* src = P.wo + (size_t)(h * DH + r * 64) * D_MODEL;
#pragma unroll
        for (int i = 0; i < 4; i++) bulk_g2s(sbase + OFF_STAGE + i * 20480, (const char*)src + i * 20480, 20480, bar_stage);
    }
    if (tid < 64) {
        float s = 0.f;
#pragma unroll
        for (int i = 0; i < 8; i++) s += wscr[i * 64 + tid];
        const bf16 qv = __float2bfloat16_rn(s);
        qs[r * 64 + tid] = qv;
        st_cluster_u16(mapa(sbase + OFF_Q + (r * 64 + tid) * 2, r ^ 1), __bfloat16_as_ushort(qv));
    }
    cluster_sync_all();

    float sc[8][2];
    {
        if (PASS == 0) { cp_async_wait_all(); __syncwarp(); }
        const uint32_t kb = sbase + OFF_K + w * (KSM_TILES * 16 * 256);
        float cacc[KSM_TILES][4];
#pragma unroll
        for (int tt = 0; tt < KSM_TILES; tt++) { cacc[tt][0] = cacc[tt][1] = cacc[tt][2] = cacc[tt][3] = 0.f; }
#pragma unroll
        for (int ks = 0; ks < 8; ks++) {
            const uint32_t b0 = *reinterpret_cast<const uint32_t*>(qs + ks * 16 + 2 * t);
            const uint32_t b1 = *reinterpret_cast<const uint32_t*>(qs + ks * 16 + 2 * t + 8);
#pragma unroll
            for (int tt = 0; tt < KSM_TILES; tt++) {
                const int row = tt * 16 + (lane & 7) + ((lane >> 3) & 1) * 8;
                const int ch = 2 * ks + (lane >> 4);
                uint32_t a[4];
                ldmatrix4(a, kb + row * 256 + ((ch ^ (row & 7)) << 4));
                mma16816(cacc[tt], a[0], a[1], a[2], a[3], b0, b1);
            }
        }
#pragma unroll
        for (int tt = 0; tt < KSM_TILES; tt++) { sc[KREG_TILES + tt][0] = cacc[tt][0]; sc[KREG_TILES + tt][1] = cacc[tt][2]; }
    }
    {
        float cacc[KREG_TILES][4];
#pragma unroll
        for (int i = 0; i < KREG_TILES; i++) { cacc[i][0] = cacc[i][1] = cacc[i][2] = cacc[i][3] = 0.f; }
#pragma unroll
        for (int j = 0; j < 4; j++) {
            const uint4 qv = *reinterpret_cast<const uint4*>(qs + j * 32 + t * 8);
#pragma unroll
            for (int i = 0; i < KREG_TILES; i++) {
                mma16816(cacc[i], kreg[i][0][j][0], kreg[i][1][j][0], kreg[i][0][j][1], kreg[i][1][j][1], qv.x, qv.y);
                mma16816(cacc[i], kreg[i][0][j][2], kreg[i][1][j][2], kreg[i][0][j][3], kreg[i][1][j][3], qv.z, qv.w);
            }
        }
#pragma unroll
        for (int i = 0; i < KREG_TILES; i++) { sc[i][0] = cacc[i][0]; sc[i][1] = cacc[i][2]; }
    }
    bf16* pw = reinterpret_cast<bf16*>(sm + OFF_WARP + w * 512);
    {
        float mx = -INFINITY;
#pragma unroll
        for (int i = 0; i < 8; i++) {
#pragma unroll
            for (int k2 = 0; k2 < 2; k2++) {
                const float s = bf16r(bf16r(sc[i][k2]) * 0.08838834764831845f);
                sc[i][k2] = s;
                mx = fmaxf(mx, s);
            }
        }
        mx = fmaxf(mx, __shfl_xor_sync(0xffffffffu, mx, 4));
        mx = fmaxf(mx, __shfl_xor_sync(0xffffffffu, mx, 8));
        mx = fmaxf(mx, __shfl_xor_sync(0xffffffffu, mx, 16));
        float l = 0.f;
#pragma unroll
        for (int i = 0; i < 8; i++) {
#pragma unroll
            for (int k2 = 0; k2 < 2; k2++) {
                const bf16 pb = __float2bfloat16_rn(exp2f((sc[i][k2] - mx) * 1.4426950408889634f));
                l += __bfloat162float(pb);
                if (t == 0) pw[i * 16 + k2 * 8 + g] = pb;
            }
        }
        l += __shfl_xor_sync(0xffffffffu, l, 4);
        l += __shfl_xor_sync(0xffffffffu, l, 8);
        l += __shfl_xor_sync(0xffffffffu, l, 16);
        if (lane == 0) { stat[2 * w] = mx; stat[2 * w + 1] = l; }
    }
    __syncthreads();
    float m_cta = stat[0];
#pragma unroll
    for (int i = 1; i < 8; i++) m_cta = fmaxf(m_cta, stat[2 * i]);
    const float wfac = exp2f((stat[2 * w] - m_cta) * 1.4426950408889634f);
    if (tid == 0) {
        float l_cta = 0.f;
#pragma unroll
        for (int i = 0; i < 8; i++) l_cta += stat[2 * i + 1] * exp2f((stat[2 * i] - m_cta) * 1.4426950408889634f);
        g_ml[PASS][b] = make_float2(m_cta, l_cta);
        st_release(&g_flag[PASS][b], epoch * 2 + PASS + 1);
    }

    float oacc[8][4];
#pragma unroll
    for (int i = 0; i < 8; i++) { oacc[i][0] = oacc[i][1] = oacc[i][2] = oacc[i][3] = 0.f; }
    {
        const bf16* vbase = P.vc + ((size_t)(h * SEQ + c * 1024 + w * 128 + 4 * t) * DH + g * 8);
        constexpr int DEPTH = (PASS == 0) ? 1 : 4;
#pragma unroll
        for (int kt0 = 0; kt0 < 8; kt0 += DEPTH) {
            uint32_t vr[DEPTH][4][2][4];
#pragma unroll
            for (int d = 0; d < DEPTH; d++)
#pragma unroll
                for (int i = 0; i < 4; i++)
#pragma unroll
                    for (int hf = 0; hf < 2; hf++)
                        ldg128(vr[d][i][hf], vbase + (size_t)((kt0 + d) * 16 + i) * DH + hf * 64);
#pragma unroll
            for (int d = 0; d < DEPTH; d++) {
                const uint2 pb = *reinterpret_cast<const uint2*>(pw + (kt0 + d) * 16 + 4 * t);
#pragma unroll
                for (int hf = 0; hf < 2; hf++)
#pragma unroll
                    for (int e = 0; e < 4; e++) {
                        const uint32_t a0 = __byte_perm(vr[d][0][hf][e], vr[d][1][hf][e], 0x5410);
                        const uint32_t a1 = __byte_perm(vr[d][0][hf][e], vr[d][1][hf][e], 0x7632);
                        const uint32_t a2 = __byte_perm(vr[d][2][hf][e], vr[d][3][hf][e], 0x5410);
                        const uint32_t a3 = __byte_perm(vr[d][2][hf][e], vr[d][3][hf][e], 0x7632);
                        mma16816(oacc[hf * 4 + e], a0, a1, a2, a3, pb.x, pb.y);
                    }
            }
        }
    }
    __syncwarp();
    {
        float* ow = reinterpret_cast<float*>(sm + OFF_WARP + w * 512);
        if (t == 0) {
#pragma unroll
            for (int hf = 0; hf < 2; hf++)
#pragma unroll
                for (int e = 0; e < 4; e++) {
                    *reinterpret_cast<float2*>(ow + hf * 64 + g * 8 + 2 * e) =
                        make_float2(oacc[hf * 4 + e][0] * wfac, oacc[hf * 4 + e][2] * wfac);
                }
        }
    }
    __syncthreads();
    if (tid < 128) {
        float mo[4], lo[4];
#pragma unroll
        for (int i = 0; i < 4; i++) {
            const int ob = (b & ~3) + i;
            unsigned it = 0;
            while (ld_acquire(&g_flag[PASS][ob]) != epoch * 2 + PASS + 1) { if (++it > SPIN_LIMIT) __trap(); }
            const float2 v = __ldcg(&g_ml[PASS][ob]);
            mo[i] = v.x; lo[i] = v.y;
        }
        const float M = fmaxf(fmaxf(mo[0], mo[1]), fmaxf(mo[2], mo[3]));
        float L = 0.f;
#pragma unroll
        for (int i = 0; i < 4; i++) L += lo[i] * exp2f((mo[i] - M) * 1.4426950408889634f);
        const float scale = exp2f((m_cta - M) * 1.4426950408889634f) / L;
        float s = 0.f;
#pragma unroll
        for (int i = 0; i < 8; i++) s += wscr[i * 128 + tid];
        s *= scale;
        const int rr = tid >> 6;
        st_cluster_f32(mapa(sbase + OFF_OEX + (r * 64 + (tid & 63)) * 4, rr), s);
    }
    cluster_sync_all();

    mbar_wait(bar_stage, 1);
    if (tid < 160) {
        float a0 = 0.f, a1 = 0.f, a2 = 0.f, a3 = 0.f;
#pragma unroll 8
        for (int row = 0; row < 64; row++) {
            const float ov = oex[row] + oex[64 + row];
            const uint2 wv = *reinterpret_cast<const uint2*>(sm + OFF_STAGE + row * 1280 + tid * 8);
            a0 += ov * bflo(wv.x); a1 += ov * bfhi(wv.x);
            a2 += ov * bflo(wv.y); a3 += ov * bfhi(wv.y);
        }
        red_add_v4(&g_acc[2 * PASS][tid * 4], a0, a1, a2, a3);
    }
    __syncthreads();
    if (PASS == 0) {
        if (tid == 0) mbar_expect_tx(bar_stage, 81920);
        __syncthreads();
        const bf16* src = P.wq + h * DH + r * 64;
        for (int row = tid; row < D_MODEL; row += NT)
            bulk_g2s(sbase + OFF_STAGE + row * 128, src + (size_t)row * (NHEAD * DH), 128, bar_stage);
    }
    grid_barrier(base + NCTA * (2 * PASS + 1));

    {
        float v[20];
#pragma unroll
        for (int i = 0; i < 20; i++) {
            const int e = lane + 32 * i;
            v[i] = bf16r(__bfloat162float(xs_cur[e]) + bf16r(__ldcg(&g_acc[2 * PASS][e])));
        }
        if (w == 1) {
#pragma unroll
            for (int i = 0; i < 20; i++) xs_mid[lane + 32 * i] = __float2bfloat16_rn(v[i]);
        }
        ln20(v);
        ln20(v);
        if (w == 0) {
#pragma unroll
            for (int i = 0; i < 20; i++) xn[lane + 32 * i] = v[i];
        }
    }
    __syncthreads();
    if (b < MLP_CTAS) {
        if (PASS == 0) { mbar_wait(sbase + OFF_BAR + 8, 0); }
        const int c2 = tid & 1, rg = tid >> 1;
        float a[8];
#pragma unroll
        for (int i = 0; i < 8; i++) a[i] = 0.f;
#pragma unroll
        for (int j = 0; j < 5; j++) {
            const int row = rg + 128 * j;
            const uint4 wv = *reinterpret_cast<const uint4*>(sm + OFF_W1 + row * 32 + c2 * 16);
            const float xv = xn[row];
            a[0] += xv * bflo(wv.x); a[1] += xv * bfhi(wv.x);
            a[2] += xv * bflo(wv.y); a[3] += xv * bfhi(wv.y);
            a[4] += xv * bflo(wv.z); a[5] += xv * bfhi(wv.z);
            a[6] += xv * bflo(wv.w); a[7] += xv * bfhi(wv.w);
        }
#pragma unroll
        for (int i = 0; i < 8; i++) {
#pragma unroll
            for (int o = 2; o <= 16; o <<= 1) a[i] += __shfl_xor_sync(0xffffffffu, a[i], o);
        }
        if (lane < 2) {
#pragma unroll
            for (int i = 0; i < 8; i++) wscr[w * 16 + c2 * 8 + i] = a[i];
        }
        __syncthreads();
        if (tid < 16) {
            float s = 0.f;
#pragma unroll
            for (int i = 0; i < 8; i++) s += wscr[i * 16 + tid];
            const float u = bf16r(bf16r(s) + __bfloat162float(P.b1[b * MLP_UNITS + tid]));
            const float inner = 0.7978845608028654f * (u + 0.044715f * u * u * u);
            hs[tid] = bf16r(0.5f * u * (1.0f + tanhf(inner)));
        }
        __syncthreads();
        if (tid < 160) {
            float a0 = 0.f, a1 = 0.f, a2 = 0.f, a3 = 0.f;
#pragma unroll
            for (int row = 0; row < MLP_UNITS; row++) {
                const float hv = hs[row];
                const uint2 wv = *reinterpret_cast<const uint2*>(sm + OFF_W2 + row * 1280 + tid * 8);
                a0 += hv * bflo(wv.x); a1 += hv * bfhi(wv.x);
                a2 += hv * bflo(wv.y); a3 += hv * bfhi(wv.y);
            }
            red_add_v4(&g_acc[2 * PASS + 1][tid * 4], a0, a1, a2, a3);
        }
    }
    if (PASS == 0) {
        grid_barrier(base + NCTA * 2);
        if (b == 0) for (int e = tid; e < D_MODEL; e += NT) g_acc[0][e] = 0.f;
        for (int e = tid; e < D_MODEL; e += NT) {
            const float o = bf16r(bf16r(__ldcg(&g_acc[1][e])) + __bfloat162float(P.b2[e]));
            xs_mid[e] = __float2bfloat16_rn(__bfloat162float(xs_mid[e]) + o);
        }
        __syncthreads();
    } else {
        __syncthreads();
        unsigned& s_last = *reinterpret_cast<unsigned*>(sm + OFF_STAT + 68);
        if (tid == 0) {
            __threadfence();
            const unsigned old = atomicAdd(&g_ctr, 1u);
            s_last = (old == base + 4 * NCTA - 1) ? 1u : 0u;
            __threadfence();
        }
        __syncthreads();
        if (s_last) {
            for (int e = tid; e < D_MODEL; e += NT) {
                const float o = bf16r(bf16r(__ldcg(&g_acc[3][e])) + __bfloat162float(P.b2[e]));
                P.out[e] = __float2bfloat16_rn(__bfloat162float(xs_mid[e]) + o);
            }
        }
    }
}

__global__ void __launch_bounds__(NT, 1) fused_kernel(const Params P) {
    extern __shared__ __align__(128) unsigned char sm[];
    const int tid = threadIdx.x, lane = tid & 31, w = tid >> 5;
    const int g = lane >> 2, t = lane & 3;
    const int b = blockIdx.x, h = b >> 2, c = b & 3, r = b & 1;
    const uint32_t sbase = smem_u32(sm);
    unsigned& s_epoch = *reinterpret_cast<unsigned*>(sm + OFF_STAT + 64);

    uint64_t pol_first;
    asm volatile("createpolicy.fractional.L2::evict_first.b64 %0, 1.0;" : "=l"(pol_first));

    if (tid == 0) {
        mbar_init(sbase + OFF_BAR, 1);
        mbar_init(sbase + OFF_BAR + 8, 1);
        asm volatile("fence.mbarrier_init.release.cluster;" ::: "memory");
        s_epoch = ld_acquire(&g_ctr) >> 9;
        mbar_expect_tx(sbase + OFF_BAR, 81920);
    }
    __syncthreads();
    const unsigned epoch = s_epoch;
    {
        const bf16* src = P.wq + h * DH + r * 64;
        for (int row = tid; row < D_MODEL; row += NT)
            bulk_g2s(sbase + OFF_STAGE + row * 128, src + (size_t)row * (NHEAD * DH), 128, sbase + OFF_BAR);
    }
    for (int e = tid; e < D_MODEL; e += NT) reinterpret_cast<bf16*>(sm + OFF_XS)[e] = P.x[e];
    if (b == 1) for (int e = tid; e < 3 * D_MODEL; e += NT) (&g_acc[1][0])[e] = 0.f;

    uint32_t kreg[KREG_TILES][2][4][4];
    {
        const bf16* kb = P.kc + ((size_t)(h * SEQ + c * 1024 + w * 128 + g) * DH + t * 8);
#pragma unroll
        for (int i = 0; i < KREG_TILES; i++)
#pragma unroll
            for (int hh = 0; hh < 2; hh++)
#pragma unroll
                for (int j = 0; j < 4; j++)
                    ldg128_hint(kreg[i][hh][j], kb + (size_t)(i * 16 + hh * 8) * DH + j * 32, pol_first);
    }
    {
        const bf16* kb = P.kc + (size_t)(h * SEQ + c * 1024 + w * 128 + KREG_TILES * 16) * DH;
        const uint32_t dst = sbase + OFF_K + w * (KSM_TILES * 16 * 256);
#pragma unroll
        for (int it = 0; it < KSM_TILES * 8; it++) {
            const int idx = it * 32 + lane;
            const int row = idx >> 4, ch = idx & 15;
            cp_async16_hint(dst + row * 256 + ((ch ^ (row & 7)) << 4), kb + (size_t)row * DH + ch * 8, pol_first);
        }
    }
    if (lane == 0) {
        const char* vsrc = (const char*)(P.vc + (size_t)(h * SEQ + c * 1024 + w * 128) * DH);
#pragma unroll
        for (int i = 0; i < 4; i++) bulk_prefetch_l2(vsrc + i * 8192, 8192);
        if (w < 5) bulk_prefetch_l2((const char*)(P.wo + (size_t)(h * DH + r * 64) * D_MODEL) + w * 16384, 16384);
    }
    if (b < MLP_CTAS) {
        if (tid == 0) {
            mbar_expect_tx(sbase + OFF_BAR + 8, 20480);
            bulk_g2s_hint(sbase + OFF_W2, P.w2 + (size_t)b * MLP_UNITS * D_MODEL, 20480, sbase + OFF_BAR + 8, pol_first);
        }
#pragma unroll
        for (int it = 0; it < 5; it++) {
            const int idx = it * NT + tid;
            const int row = idx >> 1, hf = idx & 1;
            cp_async16_hint(sbase + OFF_W1 + row * 32 + hf * 16, P.w1 + (size_t)row * FF + b * MLP_UNITS + hf * 8, pol_first);
        }
    }
    __syncthreads();

    layer_pair<0>(P, sm, kreg, epoch, pol_first);
    layer_pair<1>(P, sm, kreg, epoch, pol_first);
}

}

extern "C" void kernel_launch(void* const* d_in, const int* in_sizes, int n_in,
                              void* d_out, int out_size) {
    Params P;
    P.x = (const bf16*)d_in[0];
    P.kc = (const bf16*)d_in[1];
    P.vc = (const bf16*)d_in[2];
    P.wq = (const bf16*)d_in[3];
    P.wo = (const bf16*)d_in[4];
    P.w1 = (const bf16*)d_in[6];
    P.b1 = (const bf16*)d_in[7];
    P.w2 = (const bf16*)d_in[8];
    P.b2 = (const bf16*)d_in[9];
    P.out = (bf16*)d_out;

    cudaFuncSetAttribute(fused_kernel, cudaFuncAttributeMaxDynamicSharedMemorySize, SMEM_BYTES);

    cudaLaunchConfig_t cfg = {};
    cfg.gridDim = dim3(NCTA);
    cfg.blockDim = dim3(NT);
    cfg.dynamicSmemBytes = SMEM_BYTES;
    cfg.stream = cudaStreamPerThread;
    cudaLaunchAttribute at[2];
    at[0].id = cudaLaunchAttributeClusterDimension;
    at[0].val.clusterDim.x = 2; at[0].val.clusterDim.y = 1; at[0].val.clusterDim.z = 1;
    at[1].id = cudaLaunchAttributeCooperative;
    at[1].val.cooperative = 1;
    cfg.attrs = at;
    cfg.numAttrs = 2;
    cudaLaunchKernelEx(&cfg, fused_kernel, P);
}
```

```cpp
#include <cuda_runtime.h>
#include <cuda_bf16.h>
#include <stdint.h>

typedef __nv_bfloat16 bf16;

namespace {

constexpr int D_MODEL = 640;
constexpr int NHEAD = 32;
constexpr int SEQ = 4096;
constexpr int DH = 128;
constexpr int FF = 1728;
constexpr int NCTA = 128;
constexpr int NT = 256;
constexpr int KREG_TILES = 5;
constexpr int KSM_TILES = 3;
constexpr int MLP_UNITS = 16;
constexpr int MLP_CTAS = FF / MLP_UNITS;

constexpr int OFF_STAGE = 0;
constexpr int OFF_W2 = 81920;
constexpr int OFF_W1 = OFF_W2 + 20480;
constexpr int OFF_K = OFF_W1 + 20480;
constexpr int OFF_XS = OFF_K + 98304;
constexpr int OFF_XN = OFF_XS + 1280;
constexpr int OFF_O = OFF_XN + 1280;
constexpr int OFF_P = OFF_O + 4096;
constexpr int OFF_Q = OFF_P + 2048;
constexpr int OFF_OEX = OFF_Q + 256;
constexpr int OFF_STAT = OFF_OEX + 512;
constexpr int OFF_RED = OFF_STAT + 128;
constexpr int OFF_HS = OFF_RED + 64;
constexpr int OFF_BAR = OFF_HS + 64;
constexpr int SMEM_BYTES = OFF_BAR + 64;

constexpr unsigned SPIN_LIMIT = 1u << 24;

__device__ unsigned int g_ctr;
__device__ float g_acc[4][D_MODEL];
__device__ float2 g_ml[2][NCTA];
__device__ unsigned int g_flag[2][NCTA];

#define TS(i) do {} while (0)

struct Params {
    const bf16* x; const bf16* kc; const bf16* vc; const bf16* wq; const bf16* wo;
    const bf16* w1; const bf16* b1; const bf16* w2; const bf16* b2; bf16* out;
};

__device__ __forceinline__ float bf16r(float x) { return __bfloat162float(__float2bfloat16_rn(x)); }
__device__ __forceinline__ float bflo(uint32_t u) { return __uint_as_float(u << 16); }
__device__ __forceinline__ float bfhi(uint32_t u) { return __uint_as_float(u & 0xffff0000u); }

__device__ __forceinline__ uint32_t smem_u32(const void* p) { return (uint32_t)__cvta_generic_to_shared(p); }

__device__ __forceinline__ void mbar_init(uint32_t bar, uint32_t cnt) {
    asm volatile("mbarrier.init.shared::cta.b64 [%0], %1;" :: "r"(bar), "r"(cnt) : "memory");
}
__device__ __forceinline__ void mbar_expect_tx(uint32_t bar, uint32_t bytes) {
    asm volatile("mbarrier.arrive.expect_tx.shared::cta.b64 _, [%0], %1;" :: "r"(bar), "r"(bytes) : "memory");
}
__device__ __forceinline__ void mbar_wait(uint32_t bar, uint32_t parity) {
    unsigned it = 0;
    while (true) {
        uint32_t ok;
        asm volatile("{\n\t.reg .pred p;\n\tmbarrier.try_wait.parity.shared::cta.b64 p, [%1], %2;\n\tselp.u32 %0, 1, 0, p;\n\t}"
                     : "=r"(ok) : "r"(bar), "r"(parity) : "memory");
        if (ok) break;
        if (++it > SPIN_LIMIT) __trap();
    }
}
__device__ __forceinline__ void bulk_g2s(uint32_t dst, const void* src, uint32_t bytes, uint32_t bar) {
    asm volatile("cp.async.bulk.shared::cluster.global.mbarrier::complete_tx::bytes [%0], [%1], %2, [%3];"
                 :: "r"(dst), "l"(src), "r"(bytes), "r"(bar) : "memory");
}
__device__ __forceinline__ void bulk_g2s_hint(uint32_t dst, const void* src, uint32_t bytes, uint32_t bar, uint64_t pol) {
    asm volatile("cp.async.bulk.shared::cluster.global.mbarrier::complete_tx::bytes.L2::cache_hint [%0], [%1], %2, [%3], %4;"
                 :: "r"(dst), "l"(src), "r"(bytes), "r"(bar), "l"(pol) : "memory");
}
__device__ __forceinline__ void bulk_prefetch_l2(const void* src, uint32_t bytes) {
    asm volatile("cp.async.bulk.prefetch.L2.global [%0], %1;" :: "l"(src), "r"(bytes) : "memory");
}
__device__ __forceinline__ void bulk_prefetch_l2_hint(const void* src, uint32_t bytes, uint64_t pol) {
    asm volatile("cp.async.bulk.prefetch.L2.global.L2::cache_hint [%0], %1, %2;" :: "l"(src), "r"(bytes), "l"(pol) : "memory");
}
__device__ __forceinline__ float ex2(float x) { float y; asm("ex2.approx.ftz.f32 %0, %1;" : "=f"(y) : "f"(x)); return y; }
__device__ __forceinline__ void cp_async16_hint(uint32_t dst, const void* src, uint64_t pol) {
    asm volatile("cp.async.cg.shared.global.L2::cache_hint [%0], [%1], 16, %2;" :: "r"(dst), "l"(src), "l"(pol) : "memory");
}
__device__ __forceinline__ void cp_async_wait_all() { asm volatile("cp.async.wait_all;" ::: "memory"); }

__device__ __forceinline__ void ldg128_hint(uint32_t (&r)[4], const void* p, uint64_t pol) {
    asm volatile("ld.global.nc.L1::no_allocate.L2::cache_hint.v4.u32 {%0,%1,%2,%3}, [%4], %5;"
                 : "=r"(r[0]), "=r"(r[1]), "=r"(r[2]), "=r"(r[3]) : "l"(p), "l"(pol));
}
__device__ __forceinline__ void ldg128(uint32_t (&r)[4], const void* p) {
    asm volatile("ld.global.nc.L1::no_allocate.v4.u32 {%0,%1,%2,%3}, [%4];"
                 : "=r"(r[0]), "=r"(r[1]), "=r"(r[2]), "=r"(r[3]) : "l"(p));
}
__device__ __forceinline__ void mma16816(float (&c)[4], uint32_t a0, uint32_t a1, uint32_t a2, uint32_t a3,
                                         uint32_t b0, uint32_t b1) {
    asm volatile("mma.sync.aligned.m16n8k16.row.col.f32.bf16.bf16.f32 {%0,%1,%2,%3}, {%4,%5,%6,%7}, {%8,%9}, {%0,%1,%2,%3};"
                 : "+f"(c[0]), "+f"(c[1]), "+f"(c[2]), "+f"(c[3])
                 : "r"(a0), "r"(a1), "r"(a2), "r"(a3), "r"(b0), "r"(b1));
}
__device__ __forceinline__ void ldmatrix4(uint32_t (&r)[4], uint32_t addr) {
    asm volatile("ldmatrix.sync.aligned.m8n8.x4.shared.b16 {%0,%1,%2,%3}, [%4];"
                 : "=r"(r[0]), "=r"(r[1]), "=r"(r[2]), "=r"(r[3]) : "r"(addr) : "memory");
}
__device__ __forceinline__ void red_add_v4(float* p, float a, float b, float c, float d) {
    asm volatile("red.global.add.v4.f32 [%0], {%1,%2,%3,%4};" :: "l"(p), "f"(a), "f"(b), "f"(c), "f"(d) : "memory");
}
__device__ __forceinline__ unsigned ld_acquire(const unsigned* p) {
    unsigned v; asm volatile("ld.acquire.gpu.global.u32 %0, [%1];" : "=r"(v) : "l"(p) : "memory"); return v;
}
__device__ __forceinline__ void st_release(unsigned* p, unsigned v) {
    asm volatile("st.release.gpu.global.u32 [%0], %1;" :: "l"(p), "r"(v) : "memory");
}
__device__ __forceinline__ void cluster_sync_all() {
    asm volatile("barrier.cluster.arrive.release.aligned;\n\tbarrier.cluster.wait.acquire.aligned;" ::: "memory");
}
__device__ __forceinline__ uint32_t mapa(uint32_t addr, uint32_t rank) {
    uint32_t r; asm volatile("mapa.shared::cluster.u32 %0, %1, %2;" : "=r"(r) : "r"(addr), "r"(rank)); return r;
}
__device__ __forceinline__ void st_cluster_f32(uint32_t addr, float v) {
    asm volatile("st.shared::cluster.f32 [%0], %1;" :: "r"(addr), "f"(v) : "memory");
}
__device__ __forceinline__ void st_cluster_u16(uint32_t addr, uint16_t v) {
    asm volatile("st.shared::cluster.u16 [%0], %1;" :: "r"(addr), "h"(v) : "memory");
}
__device__ __forceinline__ float warp_sum(float v) {
#pragma unroll
    for (int o = 16; o > 0; o >>= 1) v += __shfl_xor_sync(0xffffffffu, v, o);
    return v;
}

__device__ __forceinline__ void grid_barrier(unsigned target) {
    __syncthreads();
    if (threadIdx.x == 0) {
        __threadfence();
        atomicAdd(&g_ctr, 1u);
        unsigned it = 0;
        while ((int)(ld_acquire(&g_ctr) - target) < 0) { if (++it > SPIN_LIMIT) __trap(); }
    }
    __syncthreads();
}

__device__ __forceinline__ float block_sum(float v, float* red, int lane, int w) {
    v = warp_sum(v);
    if (lane == 0) red[w] = v;
    __syncthreads();
    const float4 a = *reinterpret_cast<const float4*>(red);
    const float4 b = *reinterpret_cast<const float4*>(red + 4);
    return ((a.x + a.y) + (a.z + a.w)) + ((b.x + b.y) + (b.z + b.w));
}

constexpr float LOG2E = 1.4426950408889634f;

__global__ void __launch_bounds__(NT, 1) fused_kernel(const Params P) {
    extern __shared__ __align__(128) unsigned char sm[];
    const int tid = threadIdx.x, lane = tid & 31, w = tid >> 5;
    const int g = lane >> 2, t = lane & 3;
    const int b = blockIdx.x, h = b >> 2, c = b & 3, r = b & 1;
    const uint32_t sbase = smem_u32(sm);
    const uint32_t bar_stage = sbase + OFF_BAR;
    bf16* xs = reinterpret_cast<bf16*>(sm + OFF_XS);
    bf16* xn = reinterpret_cast<bf16*>(sm + OFF_XN);
    float* oscr = reinterpret_cast<float*>(sm + OFF_O);
    bf16* qs = reinterpret_cast<bf16*>(sm + OFF_Q);
    float* oex = reinterpret_cast<float*>(sm + OFF_OEX);
    float* stat = reinterpret_cast<float*>(sm + OFF_STAT);
    float* red = reinterpret_cast<float*>(sm + OFF_RED);
    float* hs = reinterpret_cast<float*>(sm + OFF_HS);
    volatile unsigned* s_flag = reinterpret_cast<volatile unsigned*>(sm + OFF_STAT + 64);

    TS(0);
    uint64_t pol_first;
    asm volatile("createpolicy.fractional.L2::evict_first.b64 %0, 1.0;" : "=l"(pol_first));

    if (tid == 0) {
        mbar_init(bar_stage, 1);
        mbar_init(bar_stage + 8, 1);
        asm volatile("fence.mbarrier_init.release.cluster;" ::: "memory");
        s_flag[0] = ld_acquire(&g_ctr) >> 9;
        mbar_expect_tx(bar_stage, 81920);
    }
    __syncthreads();
    const unsigned epoch = s_flag[0];
    const unsigned base = epoch << 9;
    const bf16* wq_src = P.wq + h * DH + r * 64;
    const bf16* wo_src = P.wo + (size_t)(h * DH + r * 64) * D_MODEL;
    const size_t kv_off = (size_t)(h * SEQ + c * 1024 + w * 128) * DH;
#pragma unroll 1
    for (int row = tid; row < D_MODEL; row += NT)
        bulk_g2s(sbase + OFF_STAGE + row * 128, wq_src + (size_t)row * (NHEAD * DH), 128, bar_stage);
    if (lane == 0) {
        bulk_prefetch_l2_hint(P.kc + kv_off, 32768, pol_first);
    }
    __syncthreads();
    if (lane == 0) {
        bulk_prefetch_l2(P.vc + kv_off, 32768);
        if (w < 5) bulk_prefetch_l2((const char*)wo_src + w * 16384, 16384);
    }
    if (b < MLP_CTAS) {
        if (tid == 0) {
            mbar_expect_tx(bar_stage + 8, 20480);
            bulk_g2s_hint(sbase + OFF_W2, P.w2 + (size_t)b * MLP_UNITS * D_MODEL, 20480, bar_stage + 8, pol_first);
        }
#pragma unroll 1
        for (int idx = tid; idx < 2 * D_MODEL; idx += NT) {
            const int row = idx >> 1, hf = idx & 1;
            cp_async16_hint(sbase + OFF_W1 + row * 32 + hf * 16, P.w1 + (size_t)row * FF + b * MLP_UNITS + hf * 8, pol_first);
        }
    }
    if (b == 1) for (int e = tid; e < 3 * D_MODEL; e += NT) (&g_acc[1][0])[e] = 0.f;

    uint32_t kreg[KREG_TILES][2][4][4];

#pragma unroll 1
    for (int s = 0; s < 4; s++) {
        {
            float xv[3];
#pragma unroll
            for (int i = 0; i < 3; i++) {
                const int e = tid + NT * i;
                float x = 0.f;
                if (e < D_MODEL) {
                    if (s == 0) {
                        x = __bfloat162float(P.x[e]);
                    } else {
                        float a = bf16r(__ldcg(&g_acc[s - 1][e]));
                        if (s == 2) a = bf16r(a + __bfloat162float(P.b2[e]));
                        x = bf16r(__bfloat162float(xs[e]) + a);
                    }
                    xs[e] = __float2bfloat16_rn(x);
                }
                xv[i] = x;
            }
            if (s == 2 && b == 0) {
                for (int e = tid; e < D_MODEL; e += NT) g_acc[0][e] = 0.f;
            }
#pragma unroll 1
            for (int rep = 0; rep <= (s & 1); rep++) {
                const float mean = block_sum(xv[0] + xv[1] + xv[2], red, lane, w) * (1.0f / D_MODEL);
                const float d0 = xv[0] - mean, d1 = xv[1] - mean, d2 = (tid < D_MODEL - 2 * NT) ? xv[2] - mean : 0.f;
                const float var = block_sum(d0 * d0 + d1 * d1 + d2 * d2, red + 8, lane, w) * (1.0f / D_MODEL);
                const float mb = bf16r(mean);
                const float den = bf16r(sqrtf(bf16r(bf16r(var) + 1e-5f)));
                xv[0] = bf16r(__fdividef(bf16r(xv[0] - mb), den));
                xv[1] = bf16r(__fdividef(bf16r(xv[1] - mb), den));
                xv[2] = (tid < D_MODEL - 2 * NT) ? bf16r(__fdividef(bf16r(xv[2] - mb), den)) : 0.f;
            }
#pragma unroll
            for (int i = 0; i < 3; i++) {
                const int e = tid + NT * i;
                if (e < D_MODEL) xn[e] = __float2bfloat16_rn(xv[i]);
            }
        }
        __syncthreads();
        TS(1 + s * 6);

        if (!(s & 1)) {
            const int pass = s >> 1;
            mbar_wait(bar_stage, 0);
            {
                const int cc = tid & 7, rg = tid >> 3;
                float a[8];
#pragma unroll
                for (int i = 0; i < 8; i++) a[i] = 0.f;
#pragma unroll 2
                for (int j = 0; j < 20; j++) {
                    const int row = rg + 32 * j;
                    const uint4 wv = *reinterpret_cast<const uint4*>(sm + OFF_STAGE + row * 128 + cc * 16);
                    const float xv = __bfloat162float(xn[row]);
                    a[0] += xv * bflo(wv.x); a[1] += xv * bfhi(wv.x);
                    a[2] += xv * bflo(wv.y); a[3] += xv * bfhi(wv.y);
                    a[4] += xv * bflo(wv.z); a[5] += xv * bfhi(wv.z);
                    a[6] += xv * bflo(wv.w); a[7] += xv * bfhi(wv.w);
                }
#pragma unroll
                for (int i = 0; i < 8; i++) {
                    a[i] += __shfl_xor_sync(0xffffffffu, a[i], 8);
                    a[i] += __shfl_xor_sync(0xffffffffu, a[i], 16);
                }
                if (lane < 8) {
                    *reinterpret_cast<float4*>(oscr + w * 64 + cc * 8) = make_float4(a[0], a[1], a[2], a[3]);
                    *reinterpret_cast<float4*>(oscr + w * 64 + cc * 8 + 4) = make_float4(a[4], a[5], a[6], a[7]);
                }
            }
            __syncthreads();
            if (tid == 0) {
                mbar_expect_tx(bar_stage, 81920);
                bulk_g2s(sbase + OFF_STAGE, wo_src, 40960, bar_stage);
                bulk_g2s(sbase + OFF_STAGE + 40960, (const char*)wo_src + 40960, 40960, bar_stage);
            }
            if (tid < 64) {
                float sum = 0.f;
#pragma unroll
                for (int i = 0; i < 8; i++) sum += oscr[i * 64 + tid];
                const bf16 qv = __float2bfloat16_rn(sum);
                qs[r * 64 + tid] = qv;
                st_cluster_u16(mapa(sbase + OFF_Q + (r * 64 + tid) * 2, r ^ 1), __bfloat16_as_ushort(qv));
            }
            asm volatile("barrier.cluster.arrive.release.aligned;" ::: "memory");
            const uint32_t kb = sbase + OFF_K + w * (KSM_TILES * 16 * 256);
            if (s == 0) {
                const bf16* kp = P.kc + kv_off + (g * DH + t * 8);
#pragma unroll
                for (int i = 0; i < KREG_TILES; i++)
#pragma unroll
                    for (int hh = 0; hh < 2; hh++)
#pragma unroll
                        for (int j = 0; j < 4; j++)
                            ldg128_hint(kreg[i][hh][j], kp + (i * 16 + hh * 8) * DH + j * 32, pol_first);
                const bf16* kq = P.kc + kv_off + KREG_TILES * 16 * DH;
#pragma unroll 1
                for (int it = 0; it < KSM_TILES * 8; it++) {
                    const int idx = it * 32 + lane;
                    const int row = idx >> 4, ch = idx & 15;
                    cp_async16_hint(kb + row * 256 + ((ch ^ (row & 7)) << 4), kq + row * DH + ch * 8, pol_first);
                }
            }
            asm volatile("barrier.cluster.wait.acquire.aligned;" ::: "memory");

            float sc[8][2];
            {
                float cacc[KREG_TILES][4];
#pragma unroll
                for (int i = 0; i < KREG_TILES; i++) { cacc[i][0] = cacc[i][1] = cacc[i][2] = cacc[i][3] = 0.f; }
#pragma unroll
                for (int j = 0; j < 4; j++) {
                    const uint4 qv = *reinterpret_cast<const uint4*>(qs + j * 32 + t * 8);
#pragma unroll
                    for (int i = 0; i < KREG_TILES; i++) {
                        mma16816(cacc[i], kreg[i][0][j][0], kreg[i][1][j][0], kreg[i][0][j][1], kreg[i][1][j][1], qv.x, qv.y);
                        mma16816(cacc[i], kreg[i][0][j][2], kreg[i][1][j][2], kreg[i][0][j][3], kreg[i][1][j][3], qv.z, qv.w);
                    }
                }
#pragma unroll
                for (int i = 0; i < KREG_TILES; i++) { sc[i][0] = cacc[i][0]; sc[i][1] = cacc[i][2]; }
            }
            {
                cp_async_wait_all();
                __syncwarp();
                float cacc[KSM_TILES][4];
#pragma unroll
                for (int tt = 0; tt < KSM_TILES; tt++) { cacc[tt][0] = cacc[tt][1] = cacc[tt][2] = cacc[tt][3] = 0.f; }
                const int row0 = (lane & 7) + ((lane >> 3) & 1) * 8;
#pragma unroll 1
                for (int ks = 0; ks < 8; ks++) {
                    const uint32_t b0 = *reinterpret_cast<const uint32_t*>(qs + ks * 16 + 2 * t);
                    const uint32_t b1 = *reinterpret_cast<const uint32_t*>(qs + ks * 16 + 2 * t + 8);
                    const int ch = 2 * ks + (lane >> 4);
                    const uint32_t ad = kb + row0 * 256 + ((ch ^ (lane & 7)) << 4);
#pragma unroll
                    for (int tt = 0; tt < KSM_TILES; tt++) {
                        uint32_t a[4];
                        ldmatrix4(a, ad + tt * 4096);
                        mma16816(cacc[tt], a[0], a[1], a[2], a[3], b0, b1);
                    }
                }
#pragma unroll
                for (int tt = 0; tt < KSM_TILES; tt++) { sc[KREG_TILES + tt][0] = cacc[tt][0]; sc[KREG_TILES + tt][1] = cacc[tt][2]; }
            }
            bf16* pw = reinterpret_cast<bf16*>(sm + OFF_P + w * 256);
            {
                float mx = -INFINITY;
#pragma unroll
                for (int i = 0; i < 8; i++) {
#pragma unroll
                    for (int k2 = 0; k2 < 2; k2++) {
                        const float sv = bf16r(bf16r(sc[i][k2]) * 0.08838834764831845f);
                        sc[i][k2] = sv;
                        mx = fmaxf(mx, sv);
                    }
                }
                mx = fmaxf(mx, __shfl_xor_sync(0xffffffffu, mx, 4));
                mx = fmaxf(mx, __shfl_xor_sync(0xffffffffu, mx, 8));
                mx = fmaxf(mx, __shfl_xor_sync(0xffffffffu, mx, 16));
                float l = 0.f;
#pragma unroll
                for (int i = 0; i < 8; i++) {
#pragma unroll
                    for (int k2 = 0; k2 < 2; k2++) {
                        const bf16 pb = __float2bfloat16_rn(ex2((sc[i][k2] - mx) * LOG2E));
                        l += __bfloat162float(pb);
                        if (t == 0) pw[i * 16 + k2 * 8 + g] = pb;
                    }
                }
                l += __shfl_xor_sync(0xffffffffu, l, 4);
                l += __shfl_xor_sync(0xffffffffu, l, 8);
                l += __shfl_xor_sync(0xffffffffu, l, 16);
                if (lane == 0) { stat[2 * w] = mx; stat[2 * w + 1] = l; }
            }
            __syncthreads();
            TS(2 + s * 6);
            float m_cta = stat[0];
#pragma unroll
            for (int i = 1; i < 8; i++) m_cta = fmaxf(m_cta, stat[2 * i]);
            const float wfac = ex2((stat[2 * w] - m_cta) * LOG2E);
            if (tid == 0) {
                float l_cta = 0.f;
#pragma unroll
                for (int i = 0; i < 8; i++) l_cta += stat[2 * i + 1] * ex2((stat[2 * i] - m_cta) * LOG2E);
                g_ml[pass][b] = make_float2(m_cta, l_cta);
                st_release(&g_flag[pass][b], epoch * 2 + pass + 1);
            }

            {
                const bf16* vbase = P.vc + kv_off + (4 * t) * DH + g * 8;
                float* ow = oscr + w * 128;
                float oacc[4][4];
#pragma unroll
                for (int i = 0; i < 4; i++) { oacc[i][0] = oacc[i][1] = oacc[i][2] = oacc[i][3] = 0.f; }
                uint32_t va[4][4], vb[4][4];
#pragma unroll
                for (int i = 0; i < 4; i++) ldg128(va[i], vbase + i * DH);
#pragma unroll 1
                for (int st = 0; st < 16; st += 2) {
                    {
                        const int s1 = st + 1;
                        const bf16* vp = vbase + (s1 & 7) * 16 * DH + (s1 >> 3) * 64;
#pragma unroll
                        for (int i = 0; i < 4; i++) ldg128(vb[i], vp + i * DH);
                    }
                    {
                        const uint2 pb = *reinterpret_cast<const uint2*>(pw + (st & 7) * 16 + 4 * t);
#pragma unroll
                        for (int e = 0; e < 4; e++)
                            mma16816(oacc[e], __byte_perm(va[0][e], va[1][e], 0x5410), __byte_perm(va[0][e], va[1][e], 0x7632),
                                     __byte_perm(va[2][e], va[3][e], 0x5410), __byte_perm(va[2][e], va[3][e], 0x7632), pb.x, pb.y);
                    }
                    if (st + 2 < 16) {
                        const int s2 = st + 2;
                        const bf16* vp = vbase + (s2 & 7) * 16 * DH + (s2 >> 3) * 64;
#pragma unroll
                        for (int i = 0; i < 4; i++) ldg128(va[i], vp + i * DH);
                    }
                    {
                        const uint2 pb = *reinterpret_cast<const uint2*>(pw + ((st + 1) & 7) * 16 + 4 * t);
#pragma unroll
                        for (int e = 0; e < 4; e++)
                            mma16816(oacc[e], __byte_perm(vb[0][e], vb[1][e], 0x5410), __byte_perm(vb[0][e], vb[1][e], 0x7632),
                                     __byte_perm(vb[2][e], vb[3][e], 0x5410), __byte_perm(vb[2][e], vb[3][e], 0x7632), pb.x, pb.y);
                    }
                    if ((st & 7) == 6) {
                        if (t == 0) {
                            float* o2 = ow + (st >> 3) * 64 + g * 8;
                            *reinterpret_cast<float4*>(o2) = make_float4(oacc[0][0] * wfac, oacc[0][2] * wfac, oacc[1][0] * wfac, oacc[1][2] * wfac);
                            *reinterpret_cast<float4*>(o2 + 4) = make_float4(oacc[2][0] * wfac, oacc[2][2] * wfac, oacc[3][0] * wfac, oacc[3][2] * wfac);
                        }
#pragma unroll
                        for (int i = 0; i < 4; i++) { oacc[i][0] = oacc[i][1] = oacc[i][2] = oacc[i][3] = 0.f; }
                    }
                }
            }
            __syncthreads();
            TS(3 + s * 6);
            if (tid < 128) {
                float M = -INFINITY, L = 0.f;
#pragma unroll 1
                for (int i = 0; i < 4; i++) {
                    const int ob = (b & ~3) + i;
                    unsigned it = 0;
                    while (ld_acquire(&g_flag[pass][ob]) != epoch * 2 + pass + 1) { if (++it > SPIN_LIMIT) __trap(); }
                    const float2 v = __ldcg(&g_ml[pass][ob]);
                    const float Mn = fmaxf(M, v.x);
                    L = L * ex2((M - Mn) * LOG2E) + v.y * ex2((v.x - Mn) * LOG2E);
                    M = Mn;
                }
                const float scale = __fdividef(ex2((m_cta - M) * LOG2E), L);
                float sum = 0.f;
#pragma unroll
                for (int i = 0; i < 8; i++) sum += oscr[i * 128 + tid];
                st_cluster_f32(mapa(sbase + OFF_OEX + (r * 64 + (tid & 63)) * 4, tid >> 6), sum * scale);
            }
            cluster_sync_all();
            mbar_wait(bar_stage, 1);
            TS(4 + s * 6);
            if (tid < 160) {
                float a0 = 0.f, a1 = 0.f, a2 = 0.f, a3 = 0.f;
#pragma unroll 4
                for (int row = 0; row < 64; row++) {
                    const float ov = oex[row] + oex[64 + row];
                    const uint2 wv = *reinterpret_cast<const uint2*>(sm + OFF_STAGE + row * 1280 + tid * 8);
                    a0 += ov * bflo(wv.x); a1 += ov * bfhi(wv.x);
                    a2 += ov * bflo(wv.y); a3 += ov * bfhi(wv.y);
                }
                red_add_v4(&g_acc[s][tid * 4], a0, a1, a2, a3);
            }
            if (s == 0) {
                __syncthreads();
                if (tid == 0) mbar_expect_tx(bar_stage, 81920);
                __syncthreads();
#pragma unroll 1
                for (int row = tid; row < D_MODEL; row += NT)
                    bulk_g2s(sbase + OFF_STAGE + row * 128, wq_src + (size_t)row * (NHEAD * DH), 128, bar_stage);
            }
        } else if (b < MLP_CTAS) {
            mbar_wait(bar_stage + 8, 0);
            const int c2 = tid & 1, rg = tid >> 1;
            float a[8];
#pragma unroll
            for (int i = 0; i < 8; i++) a[i] = 0.f;
#pragma unroll 1
            for (int j = 0; j < 5; j++) {
                const int row = rg + 128 * j;
                const uint4 wv = *reinterpret_cast<const uint4*>(sm + OFF_W1 + row * 32 + c2 * 16);
                const float xv = __bfloat162float(xn[row]);
                a[0] += xv * bflo(wv.x); a[1] += xv * bfhi(wv.x);
                a[2] += xv * bflo(wv.y); a[3] += xv * bfhi(wv.y);
                a[4] += xv * bflo(wv.z); a[5] += xv * bfhi(wv.z);
                a[6] += xv * bflo(wv.w); a[7] += xv * bfhi(wv.w);
            }
#pragma unroll
            for (int i = 0; i < 8; i++) {
#pragma unroll
                for (int o = 2; o <= 16; o <<= 1) a[i] += __shfl_xor_sync(0xffffffffu, a[i], o);
            }
            if (lane < 2) {
                *reinterpret_cast<float4*>(oscr + w * 16 + c2 * 8) = make_float4(a[0], a[1], a[2], a[3]);
                *reinterpret_cast<float4*>(oscr + w * 16 + c2 * 8 + 4) = make_float4(a[4], a[5], a[6], a[7]);
            }
            __syncthreads();
            if (tid < 16) {
                float sum = 0.f;
#pragma unroll
                for (int i = 0; i < 8; i++) sum += oscr[i * 16 + tid];
                const float u = bf16r(bf16r(sum) + __bfloat162float(P.b1[b * MLP_UNITS + tid]));
                const float inner = 0.7978845608028654f * (u + 0.044715f * u * u * u);
                hs[tid] = bf16r(0.5f * u * (1.0f + tanhf(inner)));
            }
            __syncthreads();
            if (tid < 160) {
                float a0 = 0.f, a1 = 0.f, a2 = 0.f, a3 = 0.f;
#pragma unroll 4
                for (int row = 0; row < MLP_UNITS; row++) {
                    const float hv = hs[row];
                    const uint2 wv = *reinterpret_cast<const uint2*>(sm + OFF_W2 + row * 1280 + tid * 8);
                    a0 += hv * bflo(wv.x); a1 += hv * bfhi(wv.x);
                    a2 += hv * bflo(wv.y); a3 += hv * bfhi(wv.y);
                }
                red_add_v4(&g_acc[s][tid * 4], a0, a1, a2, a3);
            }
        }
        TS(5 + s * 6);
        if (s < 3) grid_barrier(base + NCTA * (s + 1));
        TS(6 + s * 6);
    }
    __syncthreads();
    if (tid == 0) {
        __threadfence();
        const unsigned old = atomicAdd(&g_ctr, 1u);
        s_flag[1] = (old == base + 4 * NCTA - 1) ? 1u : 0u;
        __threadfence();
    }
    __syncthreads();
    if (s_flag[1]) {
        for (int e = tid; e < D_MODEL; e += NT) {
            const float o = bf16r(bf16r(__ldcg(&g_acc[3][e])) + __bfloat162float(P.b2[e]));
            P.out[e] = __float2bfloat16_rn(__bfloat162float(xs[e]) + o);
        }
    }
    TS(25);
}

}

extern "C" void kernel_launch(void* const* d_in, const int* in_sizes, int n_in,
                              void* d_out, int out_size) {
    Params P;
    P.x = (const bf16*)d_in[0];
    P.kc = (const bf16*)d_in[1];
    P.vc = (const bf16*)d_in[2];
    P.wq = (const bf16*)d_in[3];
    P.wo = (const bf16*)d_in[4];
    P.w1 = (const bf16*)d_in[6];
    P.b1 = (const bf16*)d_in[7];
    P.w2 = (const bf16*)d_in[8];
    P.b2 = (const bf16*)d_in[9];
    P.out = (bf16*)d_out;

    cudaFuncSetAttribute(fused_kernel, cudaFuncAttributeMaxDynamicSharedMemorySize, SMEM_BYTES);

    cudaLaunchConfig_t cfg = {};
    cfg.gridDim = dim3(NCTA);
    cfg.blockDim = dim3(NT);
    cfg.dynamicSmemBytes = SMEM_BYTES;
    cfg.stream = cudaStreamPerThread;
    cudaLaunchAttribute at[2];
    at[0].id = cudaLaunchAttributeClusterDimension;
    at[0].val.clusterDim.x = 2; at[0].val.clusterDim.y = 1; at[0].val.clusterDim.z = 1;
    at[1].id = cudaLaunchAttributeCooperative;
    at[1].val.cooperative = 1;
    cfg.attrs = at;
    cfg.numAttrs = 2;
    cudaLaunchKernelEx(&cfg, fused_kernel, P);
}
```

```cpp
#include <cuda_runtime.h>
#include <cuda_bf16.h>
#include <stdint.h>

typedef __nv_bfloat16 bf16;

namespace {

constexpr int D_MODEL = 640;
constexpr int NHEAD = 32;
constexpr int SEQ = 4096;
constexpr int DH = 128;
constexpr int FF = 1728;
constexpr int NCTA = 128;
constexpr int NT = 256;
constexpr int KREG_TILES = 5;
constexpr int KSM_TILES = 3;
constexpr int MLP_UNITS = 16;
constexpr int MLP_CTAS = FF / MLP_UNITS;

constexpr int OFF_STAGE = 0;
constexpr int OFF_W2 = 81920;
constexpr int OFF_W1 = OFF_W2 + 20480;
constexpr int OFF_K = OFF_W1 + 20480;
constexpr int OFF_XS = OFF_K + 98304;
constexpr int OFF_XN = OFF_XS + 1280;
constexpr int OFF_O = OFF_XN + 1280;
constexpr int OFF_P = OFF_O + 4096;
constexpr int OFF_Q = OFF_P + 2048;
constexpr int OFF_OEX = OFF_Q + 256;
constexpr int OFF_STAT = OFF_OEX + 512;
constexpr int OFF_RED = OFF_STAT + 80;
constexpr int OFF_HS = OFF_RED + 96;
constexpr int OFF_B2 = OFF_HS + 320;
constexpr int SMEM_BYTES = OFF_B2 + 1280;

static_assert(SMEM_BYTES <= 232448, "smem");
constexpr int NREP = 4;
constexpr unsigned SPIN_LIMIT = 1u << 24;

__device__ unsigned int g_ctr;
__device__ float g_acc[4][NREP][D_MODEL];
__device__ uint4 g_ml[2][NCTA];

#define TS(i) do {} while (0)
#define TS2(i) do {} while (0)

struct Params {
    const bf16* x; const bf16* kc; const bf16* vc; const bf16* wq; const bf16* wo;
    const bf16* w1; const bf16* b1; const bf16* w2; const bf16* b2; bf16* out;
};

__device__ __forceinline__ float bf16r(float x) { return __bfloat162float(__float2bfloat16_rn(x)); }
__device__ __forceinline__ float bflo(uint32_t u) { return __uint_as_float(u << 16); }
__device__ __forceinline__ float bfhi(uint32_t u) { return __uint_as_float(u & 0xffff0000u); }

__device__ __forceinline__ uint32_t smem_u32(const void* p) { return (uint32_t)__cvta_generic_to_shared(p); }

__device__ __forceinline__ void mbar_init(uint32_t bar, uint32_t cnt) {
    asm volatile("mbarrier.init.shared::cta.b64 [%0], %1;" :: "r"(bar), "r"(cnt) : "memory");
}
__device__ __forceinline__ void mbar_expect_tx(uint32_t bar, uint32_t bytes) {
    asm volatile("mbarrier.arrive.expect_tx.shared::cta.b64 _, [%0], %1;" :: "r"(bar), "r"(bytes) : "memory");
}
__device__ __forceinline__ void mbar_wait(uint32_t bar, uint32_t parity) {
    unsigned it = 0;
    while (true) {
        uint32_t ok;
        asm volatile("{\n\t.reg .pred p;\n\tmbarrier.try_wait.parity.shared::cta.b64 p, [%1], %2;\n\tselp.u32 %0, 1, 0, p;\n\t}"
                     : "=r"(ok) : "r"(bar), "r"(parity) : "memory");
        if (ok) break;
        if (++it > SPIN_LIMIT) __trap();
    }
}
__device__ __forceinline__ void bulk_g2s(uint32_t dst, const void* src, uint32_t bytes, uint32_t bar) {
    asm volatile("cp.async.bulk.shared::cluster.global.mbarrier::complete_tx::bytes [%0], [%1], %2, [%3];"
                 :: "r"(dst), "l"(src), "r"(bytes), "r"(bar) : "memory");
}
__device__ __forceinline__ void bulk_g2s_hint(uint32_t dst, const void* src, uint32_t bytes, uint32_t bar, uint64_t pol) {
    asm volatile("cp.async.bulk.shared::cluster.global.mbarrier::complete_tx::bytes.L2::cache_hint [%0], [%1], %2, [%3], %4;"
                 :: "r"(dst), "l"(src), "r"(bytes), "r"(bar), "l"(pol) : "memory");
}
__device__ __forceinline__ void bulk_prefetch_l2(const void* src, uint32_t bytes) {
    asm volatile("cp.async.bulk.prefetch.L2.global [%0], %1;" :: "l"(src), "r"(bytes) : "memory");
}
__device__ __forceinline__ void bulk_prefetch_l2_hint(const void* src, uint32_t bytes, uint64_t pol) {
    asm volatile("cp.async.bulk.prefetch.L2.global.L2::cache_hint [%0], %1, %2;" :: "l"(src), "r"(bytes), "l"(pol) : "memory");
}
__device__ __forceinline__ float ex2(float x) { float y; asm("ex2.approx.ftz.f32 %0, %1;" : "=f"(y) : "f"(x)); return y; }
__device__ __forceinline__ void cp_async16_hint(uint32_t dst, const void* src, uint64_t pol) {
    asm volatile("cp.async.cg.shared.global.L2::cache_hint [%0], [%1], 16, %2;" :: "r"(dst), "l"(src), "l"(pol) : "memory");
}
__device__ __forceinline__ void cp_async_wait_all() { asm volatile("cp.async.wait_all;" ::: "memory"); }
__device__ __forceinline__ void cp_async_commit() { asm volatile("cp.async.commit_group;" ::: "memory"); }
template <int N> __device__ __forceinline__ void cp_async_wait_group() { asm volatile("cp.async.wait_group %0;" :: "n"(N) : "memory"); }

__device__ __forceinline__ void ldg128_hint(uint32_t (&r)[4], const void* p, uint64_t pol) {
    asm volatile("ld.global.nc.L1::no_allocate.L2::cache_hint.v4.u32 {%0,%1,%2,%3}, [%4], %5;"
                 : "=r"(r[0]), "=r"(r[1]), "=r"(r[2]), "=r"(r[3]) : "l"(p), "l"(pol));
}
__device__ __forceinline__ void ldg128(uint32_t (&r)[4], const void* p) {
    asm volatile("ld.global.nc.v4.u32 {%0,%1,%2,%3}, [%4];"
                 : "=r"(r[0]), "=r"(r[1]), "=r"(r[2]), "=r"(r[3]) : "l"(p));
}
__device__ __forceinline__ void mma16816(float (&c)[4], uint32_t a0, uint32_t a1, uint32_t a2, uint32_t a3,
                                         uint32_t b0, uint32_t b1) {
    asm volatile("mma.sync.aligned.m16n8k16.row.col.f32.bf16.bf16.f32 {%0,%1,%2,%3}, {%4,%5,%6,%7}, {%8,%9}, {%0,%1,%2,%3};"
                 : "+f"(c[0]), "+f"(c[1]), "+f"(c[2]), "+f"(c[3])
                 : "r"(a0), "r"(a1), "r"(a2), "r"(a3), "r"(b0), "r"(b1));
}
__device__ __forceinline__ void ldmatrix4(uint32_t (&r)[4], uint32_t addr) {
    asm volatile("ldmatrix.sync.aligned.m8n8.x4.shared.b16 {%0,%1,%2,%3}, [%4];"
                 : "=r"(r[0]), "=r"(r[1]), "=r"(r[2]), "=r"(r[3]) : "r"(addr) : "memory");
}
__device__ __forceinline__ void red_add_v4(float* p, float a, float b, float c, float d) {
    asm volatile("red.global.add.v4.f32 [%0], {%1,%2,%3,%4};" :: "l"(p), "f"(a), "f"(b), "f"(c), "f"(d) : "memory");
}
__device__ __forceinline__ unsigned ld_acquire(const unsigned* p) {
    unsigned v; asm volatile("ld.acquire.gpu.global.u32 %0, [%1];" : "=r"(v) : "l"(p) : "memory"); return v;
}
__device__ __forceinline__ void st_release(unsigned* p, unsigned v) {
    asm volatile("st.release.gpu.global.u32 [%0], %1;" :: "l"(p), "r"(v) : "memory");
}
__device__ __forceinline__ void cluster_sync_all() {
    asm volatile("barrier.cluster.arrive.release.aligned;\n\tbarrier.cluster.wait.acquire.aligned;" ::: "memory");
}
__device__ __forceinline__ uint32_t mapa(uint32_t addr, uint32_t rank) {
    uint32_t r; asm volatile("mapa.shared::cluster.u32 %0, %1, %2;" : "=r"(r) : "r"(addr), "r"(rank)); return r;
}
__device__ __forceinline__ void st_cluster_f32(uint32_t addr, float v) {
    asm volatile("st.shared::cluster.f32 [%0], %1;" :: "r"(addr), "f"(v) : "memory");
}
__device__ __forceinline__ void st_cluster_u16(uint32_t addr, uint16_t v) {
    asm volatile("st.shared::cluster.u16 [%0], %1;" :: "r"(addr), "h"(v) : "memory");
}
__device__ __forceinline__ float warp_sum(float v) {
#pragma unroll
    for (int o = 16; o > 0; o >>= 1) v += __shfl_xor_sync(0xffffffffu, v, o);
    return v;
}

__device__ __forceinline__ void grid_barrier(unsigned target) {
    __syncthreads();
    if (threadIdx.x == 0) {
        __threadfence();
        atomicAdd(&g_ctr, 1u);
        unsigned it = 0;
        while ((int)(ld_acquire(&g_ctr) - target) < 0) { if (++it > SPIN_LIMIT) __trap(); }
    }
    __syncthreads();
}

constexpr float LOG2E = 1.4426950408889634f;

__device__ __forceinline__ void ldmatrix4t(uint32_t (&r)[4], uint32_t addr) {
    asm volatile("ldmatrix.sync.aligned.m8n8.x4.trans.shared.b16 {%0,%1,%2,%3}, [%4];"
                 : "=r"(r[0]), "=r"(r[1]), "=r"(r[2]), "=r"(r[3]) : "r"(addr) : "memory");
}
__device__ __forceinline__ void red_add(float* p, float a) {
    asm volatile("red.global.add.f32 [%0], %1;" :: "l"(p), "f"(a) : "memory");
}
__device__ __forceinline__ uint32_t pack_bf16(float lo, float hi) {
    uint32_t r; asm("cvt.rn.bf16x2.f32 %0, %1, %2;" : "=r"(r) : "f"(hi), "f"(lo)); return r;
}

__global__ void __launch_bounds__(NT, 1) fused_kernel(const Params P) {
    extern __shared__ __align__(128) unsigned char sm[];
    const int tid = threadIdx.x, lane = tid & 31, w = tid >> 5;
    const int g = lane >> 2, t = lane & 3;
    const int b = blockIdx.x, h = b >> 2, c = b & 3, r = b & 1;
    const uint32_t sbase = smem_u32(sm);
    bf16* xs = reinterpret_cast<bf16*>(sm + OFF_XS);
    bf16* xn = reinterpret_cast<bf16*>(sm + OFF_XN);
    bf16* b2s = reinterpret_cast<bf16*>(sm + OFF_B2);
    float* oscr = reinterpret_cast<float*>(sm + OFF_O);
    bf16* qs = reinterpret_cast<bf16*>(sm + OFF_Q);
    float* oex = reinterpret_cast<float*>(sm + OFF_OEX);
    float* stat = reinterpret_cast<float*>(sm + OFF_STAT);
    float* red = reinterpret_cast<float*>(sm + OFF_RED);
    bf16* hs = reinterpret_cast<bf16*>(sm + OFF_HS);
    volatile unsigned* s_flag = reinterpret_cast<volatile unsigned*>(sm + OFF_STAT + 64);

    TS(0);
    if (tid < D_MODEL / 8) *reinterpret_cast<uint4*>(xs + tid * 8) = __ldg(reinterpret_cast<const uint4*>(P.x) + tid);
    else if (tid < D_MODEL / 4) *reinterpret_cast<uint4*>(b2s + (tid - 80) * 8) = __ldg(reinterpret_cast<const uint4*>(P.b2) + (tid - 80));
    else if (tid < 162) { if (b < MLP_CTAS) *reinterpret_cast<uint4*>(hs + 16 + (tid - 160) * 8) = __ldg(reinterpret_cast<const uint4*>(P.b1 + b * MLP_UNITS) + (tid - 160)); }
    else if (tid == 192) s_flag[0] = ld_acquire(&g_ctr) >> 9;
    uint64_t pol_first;
    asm volatile("createpolicy.fractional.L2::evict_first.b64 %0, 1.0;" : "=l"(pol_first));

    const bf16* wq_src = P.wq + h * DH + r * 64;
    const bf16* wo_src = P.wo + (size_t)(h * DH + r * 64) * D_MODEL;
    const size_t kv_off = (size_t)(h * SEQ + c * 1024 + w * 128) * DH;
#pragma unroll 1
    for (int idx = tid; idx < D_MODEL * 8; idx += NT)
        cp_async16_hint(sbase + OFF_STAGE + (idx >> 3) * 128 + (((idx ^ (idx >> 3)) & 7) << 4),
                        wq_src + (size_t)(idx >> 3) * (NHEAD * DH) + (idx & 7) * 8, pol_first);
    cp_async_commit();
    const uint32_t kb = sbase + OFF_K + w * (KSM_TILES * 16 * 256);
    {
        const bf16* kq = P.kc + kv_off + KREG_TILES * 16 * DH;
#pragma unroll 1
        for (int it = 0; it < KSM_TILES * 8; it++) {
            const int idx = it * 32 + lane;
            const int row = idx >> 4, ch = idx & 15;
            cp_async16_hint(kb + row * 256 + ((ch ^ (row & 7)) << 4), kq + row * DH + ch * 8, pol_first);
        }
    }
    cp_async_commit();
    if (b < MLP_CTAS) {
#pragma unroll 1
        for (int idx = tid; idx < 2 * D_MODEL; idx += NT) {
            const int row = idx >> 1, hf = idx & 1;
            cp_async16_hint(sbase + OFF_W1 + row * 32 + hf * 16, P.w1 + (size_t)row * FF + b * MLP_UNITS + hf * 8, pol_first);
            const int r2 = idx / 80, ch = idx - r2 * 80;
            cp_async16_hint(sbase + OFF_W2 + r2 * 1280 + ((ch ^ (r2 & 7)) << 4), P.w2 + (size_t)(b * MLP_UNITS) * D_MODEL + idx * 8, pol_first);
        }
    }
    cp_async_commit();
    if (b == 1) for (int e = tid; e < 3 * NREP * D_MODEL; e += NT) (&g_acc[1][0][0])[e] = 0.f;
    uint32_t kreg[KREG_TILES][2][4][4];
    __syncthreads();
    const unsigned epoch = s_flag[0];
    const unsigned base = epoch << 9;

#pragma unroll 1
    for (int s = 0; s < 4; s++) {
        {
            float v[4] = {0.f, 0.f, 0.f, 0.f};
            if (tid < D_MODEL / 4) {
                const uint2 xr = *reinterpret_cast<const uint2*>(xs + tid * 4);
                v[0] = bflo(xr.x); v[1] = bfhi(xr.x); v[2] = bflo(xr.y); v[3] = bfhi(xr.y);
                if (s != 0) {
                    float4 a = __ldcg(reinterpret_cast<const float4*>(&g_acc[s - 1][0][0]) + tid);
#pragma unroll
                    for (int i = 1; i < NREP; i++) {
                        const float4 a2 = __ldcg(reinterpret_cast<const float4*>(&g_acc[s - 1][i][0]) + tid);
                        a.x += a2.x; a.y += a2.y; a.z += a2.z; a.w += a2.w;
                    }
                    a.x = bf16r(a.x); a.y = bf16r(a.y); a.z = bf16r(a.z); a.w = bf16r(a.w);
                    if (s == 2) {
                        const uint2 br = *reinterpret_cast<const uint2*>(b2s + tid * 4);
                        a.x = bf16r(a.x + bflo(br.x)); a.y = bf16r(a.y + bfhi(br.x));
                        a.z = bf16r(a.z + bflo(br.y)); a.w = bf16r(a.w + bfhi(br.y));
                    }
                    v[0] = bf16r(v[0] + a.x); v[1] = bf16r(v[1] + a.y); v[2] = bf16r(v[2] + a.z); v[3] = bf16r(v[3] + a.w);
                    *reinterpret_cast<uint2*>(xs + tid * 4) = make_uint2(pack_bf16(v[0], v[1]), pack_bf16(v[2], v[3]));
                }
            }
            if (s == 2 && b == 0) {
                for (int e = tid; e < NREP * D_MODEL; e += NT) (&g_acc[0][0][0])[e] = 0.f;
            }
#pragma unroll 1
            for (int rep = 0; rep <= (s & 1); rep++) {
                float mean = 0.25f * ((v[0] + v[1]) + (v[2] + v[3]));
                float m2 = (v[0] - mean) * (v[0] - mean) + (v[1] - mean) * (v[1] - mean) +
                           (v[2] - mean) * (v[2] - mean) + (v[3] - mean) * (v[3] - mean);
                float hn = 2.f;
#pragma unroll
                for (int o = 1; o < 32; o <<= 1) {
                    const float mo = __shfl_xor_sync(0xffffffffu, mean, o);
                    const float qo = __shfl_xor_sync(0xffffffffu, m2, o);
                    const float d = mo - mean;
                    m2 = m2 + qo + d * d * hn;
                    mean = 0.5f * (mean + mo);
                    hn *= 2.f;
                }
                float* rd = red + rep * 12;
                if (lane == 0 && w < 5) { rd[2 * w] = mean; rd[2 * w + 1] = m2; }
                __syncthreads();
                float gm = 0.f, gq = 0.f;
#pragma unroll
                for (int i = 0; i < 5; i++) { gm += rd[2 * i]; gq += rd[2 * i + 1]; }
                gm *= 0.2f;
#pragma unroll
                for (int i = 0; i < 5; i++) { const float d = rd[2 * i] - gm; gq += 128.f * d * d; }
                const float mb = bf16r(gm);
                const float den = bf16r(sqrtf(bf16r(bf16r(gq * (1.0f / D_MODEL)) + 1e-5f)));
#pragma unroll
                for (int i = 0; i < 4; i++) v[i] = bf16r(__fdividef(bf16r(v[i] - mb), den));
            }
            if (tid < D_MODEL / 4)
                *reinterpret_cast<uint2*>(xn + tid * 4) = make_uint2(pack_bf16(v[0], v[1]), pack_bf16(v[2], v[3]));
        }
        if (s == 0) cp_async_wait_group<2>();
        else if (s == 1) cp_async_wait_group<1>();
        else if (s == 2) cp_async_wait_all();
        __syncthreads();
        TS(1 + s * 6);
        float* acc = &g_acc[s][b & (NREP - 1)][0];

        if (!(s & 1)) {
            const int pass = s >> 1;
            {
                float cq[4][4];
#pragma unroll
                for (int i = 0; i < 4; i++) { cq[i][0] = cq[i][1] = cq[i][2] = cq[i][3] = 0.f; }
#pragma unroll 1
                for (int k5 = 0; k5 < 5; k5++) {
                    const int ks = w * 5 + k5;
                    const uint32_t b0 = *reinterpret_cast<const uint32_t*>(xn + ks * 16 + 2 * t);
                    const uint32_t b1 = *reinterpret_cast<const uint32_t*>(xn + ks * 16 + 2 * t + 8);
                    const int krow = ks * 16 + (lane & 7) + ((lane >> 4) & 1) * 8;
#pragma unroll
                    for (int mt = 0; mt < 4; mt++) {
                        uint32_t a[4];
                        ldmatrix4t(a, sbase + OFF_STAGE + krow * 128 + (((2 * mt + ((lane >> 3) & 1)) ^ (lane & 7)) << 4));
                        mma16816(cq[mt], a[0], a[1], a[2], a[3], b0, b1);
                    }
                }
                if (t == 0) {
#pragma unroll
                    for (int mt = 0; mt < 4; mt++) { oscr[w * 64 + mt * 16 + g] = cq[mt][0]; oscr[w * 64 + mt * 16 + 8 + g] = cq[mt][2]; }
                }
            }
            TS2(1);
            __syncthreads();
            if (tid < 64) {
                float sum = 0.f;
#pragma unroll
                for (int i = 0; i < 8; i++) sum += oscr[i * 64 + tid];
                const bf16 qv = __float2bfloat16_rn(sum);
                qs[r * 64 + tid] = qv;
                st_cluster_u16(mapa(sbase + OFF_Q + (r * 64 + tid) * 2, r ^ 1), __bfloat16_as_ushort(qv));
            }
            asm volatile("barrier.cluster.arrive.release.aligned;" ::: "memory");
#pragma unroll 1
            for (int idx = tid; idx < 64 * 80; idx += NT) {
                const int row = idx / 80, ch = idx - row * 80;
                cp_async16_hint(sbase + OFF_STAGE + row * 1280 + ((ch ^ (row & 7)) << 4), wo_src + idx * 8, pol_first);
            }
            cp_async_commit();
            if (s == 0) {
                const bf16* kp = P.kc + kv_off + (g * DH + t * 8);
#pragma unroll
                for (int i = 0; i < KREG_TILES; i++)
#pragma unroll
                    for (int hh = 0; hh < 2; hh++)
#pragma unroll
                        for (int j = 0; j < 4; j++)
                            ldg128_hint(kreg[i][hh][j], kp + (i * 16 + hh * 8) * DH + j * 32, pol_first);
            }
            TS2(3);
            asm volatile("barrier.cluster.wait.acquire.aligned;" ::: "memory");
            TS2(4);

            float sc[8][2];
            {
                float cacc[KREG_TILES][4];
#pragma unroll
                for (int i = 0; i < KREG_TILES; i++) { cacc[i][0] = cacc[i][1] = cacc[i][2] = cacc[i][3] = 0.f; }
#pragma unroll
                for (int j = 0; j < 4; j++) {
                    const uint4 qv = *reinterpret_cast<const uint4*>(qs + j * 32 + t * 8);
#pragma unroll
                    for (int i = 0; i < KREG_TILES; i++) {
                        mma16816(cacc[i], kreg[i][0][j][0], kreg[i][1][j][0], kreg[i][0][j][1], kreg[i][1][j][1], qv.x, qv.y);
                        mma16816(cacc[i], kreg[i][0][j][2], kreg[i][1][j][2], kreg[i][0][j][3], kreg[i][1][j][3], qv.z, qv.w);
                    }
                }
#pragma unroll
                for (int i = 0; i < KREG_TILES; i++) { sc[i][0] = cacc[i][0]; sc[i][1] = cacc[i][2]; }
            }
            {
                TS2(5);
                if (s == 0) {
                    if (lane == 0) bulk_prefetch_l2(P.vc + kv_off, 32768);
                    cp_async_wait_group<2>();
                    __syncwarp();
                }
                float cacc[KSM_TILES][4];
#pragma unroll
                for (int tt = 0; tt < KSM_TILES; tt++) { cacc[tt][0] = cacc[tt][1] = cacc[tt][2] = cacc[tt][3] = 0.f; }
                const int row0 = (lane & 7) + ((lane >> 3) & 1) * 8;
#pragma unroll 4
                for (int ks = 0; ks < 8; ks++) {
                    const uint32_t b0 = *reinterpret_cast<const uint32_t*>(qs + ks * 16 + 2 * t);
                    const uint32_t b1 = *reinterpret_cast<const uint32_t*>(qs + ks * 16 + 2 * t + 8);
                    const int ch = 2 * ks + (lane >> 4);
                    const uint32_t ad = kb + row0 * 256 + ((ch ^ (lane & 7)) << 4);
#pragma unroll
                    for (int tt = 0; tt < KSM_TILES; tt++) {
                        uint32_t a[4];
                        ldmatrix4(a, ad + tt * 4096);
                        mma16816(cacc[tt], a[0], a[1], a[2], a[3], b0, b1);
                    }
                }
#pragma unroll
                for (int tt = 0; tt < KSM_TILES; tt++) { sc[KREG_TILES + tt][0] = cacc[tt][0]; sc[KREG_TILES + tt][1] = cacc[tt][2]; }
            }
            TS2(6);
            bf16* pw = reinterpret_cast<bf16*>(sm + OFF_P + w * 256);
            {
                float s4[4];
#pragma unroll
                for (int q2 = 0; q2 < 4; q2++) {
                    const int i = q2 >> 1, k2 = q2 & 1;
                    const float v01 = (t & 1) ? sc[2 + i][k2] : sc[i][k2];
                    const float v23 = (t & 1) ? sc[6 + i][k2] : sc[4 + i][k2];
                    s4[q2] = (t & 2) ? v23 : v01;
                }
                float mx = -INFINITY;
#pragma unroll
                for (int q2 = 0; q2 < 4; q2++) {
                    s4[q2] = bf16r(bf16r(s4[q2]) * 0.08838834764831845f);
                    mx = fmaxf(mx, s4[q2]);
                }
#pragma unroll
                for (int o = 1; o < 32; o <<= 1) mx = fmaxf(mx, __shfl_xor_sync(0xffffffffu, mx, o));
                float l = 0.f;
#pragma unroll
                for (int q2 = 0; q2 < 4; q2++) {
                    const bf16 pb = __float2bfloat16_rn(ex2((s4[q2] - mx) * LOG2E));
                    l += __bfloat162float(pb);
                    pw[(2 * t + (q2 >> 1)) * 16 + (q2 & 1) * 8 + g] = pb;
                }
                l = warp_sum(l);
                if (lane == 0) { stat[2 * w] = mx; stat[2 * w + 1] = l; }
            }
            TS2(7);
            __syncthreads();
            TS(2 + s * 6);
            float m_cta = stat[0];
#pragma unroll
            for (int i = 1; i < 8; i++) m_cta = fmaxf(m_cta, stat[2 * i]);
            const float wfac = ex2((stat[2 * w] - m_cta) * LOG2E);
            if (tid == 0) {
                float l_cta = 0.f;
#pragma unroll
                for (int i = 0; i < 8; i++) l_cta += stat[2 * i + 1] * ex2((stat[2 * i] - m_cta) * LOG2E);
                asm volatile("st.relaxed.gpu.global.v4.u32 [%0], {%1,%2,%3,%4};" :: "l"(&g_ml[pass][b]),
                             "r"(__float_as_uint(m_cta)), "r"(__float_as_uint(l_cta)), "r"(epoch * 2 + pass + 1), "r"(0u) : "memory");
            }

            {
                const bf16* vbase = P.vc + kv_off + (4 * t) * DH + g * 8;
                float* ow = oscr + w * 128;
                float oacc[4][4];
#pragma unroll
                for (int i = 0; i < 4; i++) { oacc[i][0] = oacc[i][1] = oacc[i][2] = oacc[i][3] = 0.f; }
                uint32_t va[4][4], vb[4][4];
#pragma unroll
                for (int i = 0; i < 4; i++) ldg128(va[i], vbase + i * DH);
#pragma unroll 1
                for (int st = 0; st < 16; st += 2) {
                    {
                        const int s1 = st + 1;
                        const bf16* vp = vbase + (s1 & 7) * 16 * DH + (s1 >> 3) * 64;
#pragma unroll
                        for (int i = 0; i < 4; i++) ldg128(vb[i], vp + i * DH);
                    }
                    {
                        const uint2 pb = *reinterpret_cast<const uint2*>(pw + (st & 7) * 16 + 4 * t);
#pragma unroll
                        for (int e = 0; e < 4; e++)
                            mma16816(oacc[e], __byte_perm(va[0][e], va[1][e], 0x5410), __byte_perm(va[0][e], va[1][e], 0x7632),
                                     __byte_perm(va[2][e], va[3][e], 0x5410), __byte_perm(va[2][e], va[3][e], 0x7632), pb.x, pb.y);
                    }
                    if (st + 2 < 16) {
                        const int s2 = st + 2;
                        const bf16* vp = vbase + (s2 & 7) * 16 * DH + (s2 >> 3) * 64;
#pragma unroll
                        for (int i = 0; i < 4; i++) ldg128(va[i], vp + i * DH);
                    }
                    {
                        const uint2 pb = *reinterpret_cast<const uint2*>(pw + ((st + 1) & 7) * 16 + 4 * t);
#pragma unroll
                        for (int e = 0; e < 4; e++)
                            mma16816(oacc[e], __byte_perm(vb[0][e], vb[1][e], 0x5410), __byte_perm(vb[0][e], vb[1][e], 0x7632),
                                     __byte_perm(vb[2][e], vb[3][e], 0x5410), __byte_perm(vb[2][e], vb[3][e], 0x7632), pb.x, pb.y);
                    }
                    if ((st & 7) == 6) {
                        if (t == 0) {
                            float* o2 = ow + (st >> 3) * 64 + g * 8;
                            *reinterpret_cast<float4*>(o2) = make_float4(oacc[0][0] * wfac, oacc[0][2] * wfac, oacc[1][0] * wfac, oacc[1][2] * wfac);
                            *reinterpret_cast<float4*>(o2 + 4) = make_float4(oacc[2][0] * wfac, oacc[2][2] * wfac, oacc[3][0] * wfac, oacc[3][2] * wfac);
                        }
#pragma unroll
                        for (int i = 0; i < 4; i++) { oacc[i][0] = oacc[i][1] = oacc[i][2] = oacc[i][3] = 0.f; }
                    }
                }
            }
            __syncthreads();
            TS(3 + s * 6);
            if (tid < 128) {
                uint4 rec[4];
                {
                    unsigned it = 0;
                    const unsigned tag = epoch * 2 + pass + 1;
                    while (true) {
#pragma unroll
                        for (int i = 0; i < 4; i++)
                            asm volatile("ld.relaxed.gpu.global.v4.u32 {%0,%1,%2,%3}, [%4];"
                                         : "=r"(rec[i].x), "=r"(rec[i].y), "=r"(rec[i].z), "=r"(rec[i].w)
                                         : "l"(&g_ml[pass][(b & ~3) + i]) : "memory");
                        if (rec[0].z == tag && rec[1].z == tag && rec[2].z == tag && rec[3].z == tag) break;
                        if (++it > SPIN_LIMIT) __trap();
                    }
                }
                const float M = fmaxf(fmaxf(__uint_as_float(rec[0].x), __uint_as_float(rec[1].x)),
                                      fmaxf(__uint_as_float(rec[2].x), __uint_as_float(rec[3].x)));
                float L = 0.f;
#pragma unroll
                for (int i = 0; i < 4; i++) L += __uint_as_float(rec[i].y) * ex2((__uint_as_float(rec[i].x) - M) * LOG2E);
                const float scale = __fdividef(ex2((m_cta - M) * LOG2E), L);
                float sum = 0.f;
#pragma unroll
                for (int i = 0; i < 8; i++) sum += oscr[i * 128 + tid];
                st_cluster_f32(mapa(sbase + OFF_OEX + (r * 64 + (tid & 63)) * 4, tid >> 6), sum * scale);
            }
            TS2(8);
            cluster_sync_all();
            TS2(9);
            if (tid < 64) {
                const float o = oex[tid] + oex[64 + tid];
                const bf16 hi = __float2bfloat16_rn(o);
                hs[32 + tid] = hi;
                hs[96 + tid] = __float2bfloat16_rn(o - __bfloat162float(hi));
            }
            cp_async_wait_all();
            __syncthreads();
            TS(4 + s * 6);
            {
                float co[5][4];
#pragma unroll
                for (int i = 0; i < 5; i++) { co[i][0] = co[i][1] = co[i][2] = co[i][3] = 0.f; }
#pragma unroll 1
                for (int ks = 0; ks < 4; ks++) {
                    uint32_t b0 = 0, b1 = 0;
                    if (g < 2) {
                        b0 = *reinterpret_cast<const uint32_t*>(hs + 32 + g * 64 + ks * 16 + 2 * t);
                        b1 = *reinterpret_cast<const uint32_t*>(hs + 32 + g * 64 + ks * 16 + 2 * t + 8);
                    }
                    const int krow = ks * 16 + (lane & 7) + ((lane >> 4) & 1) * 8;
#pragma unroll
                    for (int i = 0; i < 5; i++) {
                        const int ch = 2 * (w * 5 + i) + ((lane >> 3) & 1);
                        uint32_t a[4];
                        ldmatrix4t(a, sbase + OFF_STAGE + krow * 1280 + ((ch ^ (lane & 7)) << 4));
                        mma16816(co[i], a[0], a[1], a[2], a[3], b0, b1);
                    }
                }
                if (t == 0) {
#pragma unroll
                    for (int i = 0; i < 5; i++) {
                        red_add(acc + (w * 5 + i) * 16 + g, co[i][0] + co[i][1]);
                        red_add(acc + (w * 5 + i) * 16 + 8 + g, co[i][2] + co[i][3]);
                    }
                }
            }
            if (s == 0) {
                __syncthreads();
#pragma unroll 1
                for (int idx = tid; idx < D_MODEL * 8; idx += NT)
                    cp_async16_hint(sbase + OFF_STAGE + (idx >> 3) * 128 + (((idx ^ (idx >> 3)) & 7) << 4),
                                    wq_src + (size_t)(idx >> 3) * (NHEAD * DH) + (idx & 7) * 8, pol_first);
                cp_async_commit();
            }
        } else if (b < MLP_CTAS) {
            {
                float ch4[4] = {0.f, 0.f, 0.f, 0.f};
#pragma unroll
                for (int k5 = 0; k5 < 5; k5++) {
                    const int ks = w * 5 + k5;
                    const uint32_t b0 = *reinterpret_cast<const uint32_t*>(xn + ks * 16 + 2 * t);
                    const uint32_t b1 = *reinterpret_cast<const uint32_t*>(xn + ks * 16 + 2 * t + 8);
                    const int krow = ks * 16 + (lane & 7) + ((lane >> 4) & 1) * 8;
                    uint32_t a[4];
                    ldmatrix4t(a, sbase + OFF_W1 + krow * 32 + ((lane >> 3) & 1) * 16);
                    mma16816(ch4, a[0], a[1], a[2], a[3], b0, b1);
                }
                if (t == 0) { oscr[w * 16 + g] = ch4[0]; oscr[w * 16 + 8 + g] = ch4[2]; }
            }
            __syncthreads();
            if (tid < 16) {
                float sum = 0.f;
#pragma unroll
                for (int i = 0; i < 8; i++) sum += oscr[i * 16 + tid];
                const float u = bf16r(bf16r(sum) + __bfloat162float(hs[16 + tid]));
                const float inner = 0.7978845608028654f * (u + 0.044715f * u * u * u);
                hs[tid] = __float2bfloat16_rn(0.5f * u * (1.0f + tanhf(inner)));
            }
            __syncthreads();
            {
                const uint32_t b0 = *reinterpret_cast<const uint32_t*>(hs + 2 * t);
                const uint32_t b1 = *reinterpret_cast<const uint32_t*>(hs + 2 * t + 8);
                const int krow = (lane & 7) + ((lane >> 4) & 1) * 8;
#pragma unroll
                for (int i = 0; i < 5; i++) {
                    const int ch = 2 * (w * 5 + i) + ((lane >> 3) & 1);
                    uint32_t a[4];
                    float co[4] = {0.f, 0.f, 0.f, 0.f};
                    ldmatrix4t(a, sbase + OFF_W2 + krow * 1280 + ((ch ^ (lane & 7)) << 4));
                    mma16816(co, a[0], a[1], a[2], a[3], b0, b1);
                    if (t == 0) {
                        red_add(acc + (w * 5 + i) * 16 + g, co[0]);
                        red_add(acc + (w * 5 + i) * 16 + 8 + g, co[2]);
                    }
                }
            }
        }
        TS(5 + s * 6);
        if (s < 3) grid_barrier(base + NCTA * (s + 1));
        TS(6 + s * 6);
    }
    __syncthreads();
    if (tid == 0) {
        __threadfence();
        const unsigned old = atomicAdd(&g_ctr, 1u);
        s_flag[1] = (old == base + 4 * NCTA - 1) ? 1u : 0u;
        __threadfence();
    }
    __syncthreads();
    if (s_flag[1]) {
        for (int e = tid; e < D_MODEL; e += NT) {
            float a = 0.f;
#pragma unroll
            for (int i = 0; i < NREP; i++) a += __ldcg(&g_acc[3][i][e]);
            const float o = bf16r(bf16r(a) + __bfloat162float(b2s[e]));
            P.out[e] = __float2bfloat16_rn(__bfloat162float(xs[e]) + o);
        }
    }
    TS(25);
}

}

extern "C" void kernel_launch(void* const* d_in, const int* in_sizes, int n_in,
                              void* d_out, int out_size) {
    Params P;
    P.x = (const bf16*)d_in[0];
    P.kc = (const bf16*)d_in[1];
    P.vc = (const bf16*)d_in[2];
    P.wq = (const bf16*)d_in[3];
    P.wo = (const bf16*)d_in[4];
    P.w1 = (const bf16*)d_in[6];
    P.b1 = (const bf16*)d_in[7];
    P.w2 = (const bf16*)d_in[8];
    P.b2 = (const bf16*)d_in[9];
    P.out = (bf16*)d_out;

    cudaFuncSetAttribute(fused_kernel, cudaFuncAttributeMaxDynamicSharedMemorySize, SMEM_BYTES);

    cudaLaunchConfig_t cfg = {};
    cfg.gridDim = dim3(NCTA);
    cfg.blockDim = dim3(NT);
    cfg.dynamicSmemBytes = SMEM_BYTES;
    cfg.stream = cudaStreamPerThread;
    cudaLaunchAttribute at[2];
    at[0].id = cudaLaunchAttributeClusterDimension;
    at[0].val.clusterDim.x = 2; at[0].val.clusterDim.y = 1; at[0].val.clusterDim.z = 1;
    at[1].id = cudaLaunchAttributeCooperative;
    at[1].val.cooperative = 1;
    cfg.attrs = at;
    cfg.numAttrs = 2;
    cudaLaunchKernelEx(&cfg, fused_kernel, P);
}
```

```cpp
#include <cuda_runtime.h>
#include <cuda.h>
#include <cuda_bf16.h>
#include <stdint.h>

typedef __nv_bfloat16 bf16;

namespace {

constexpr int D_MODEL = 640;
constexpr int NHEAD = 32;
constexpr int SEQ = 4096;
constexpr int DH = 128;
constexpr int FF = 1728;
constexpr int NCTA = 128;
constexpr int NT = 256;
constexpr int KREG_TILES = 5;
constexpr int KSM_TILES = 3;
constexpr int MLP_UNITS = 16;
constexpr int MLP_CTAS = FF / MLP_UNITS;

constexpr int OFF_STAGE = 0;
constexpr int OFF_W2 = 81920;
constexpr int OFF_W1 = OFF_W2 + 20480;
constexpr int OFF_K = OFF_W1 + 20480;
constexpr int OFF_XS = OFF_K + 98304;
constexpr int OFF_XN = OFF_XS + 1280;
constexpr int OFF_O = OFF_XN + 1280;
constexpr int OFF_P = OFF_O + 4096;
constexpr int OFF_Q = OFF_P + 2048;
constexpr int OFF_OEX = OFF_Q + 256;
constexpr int OFF_STAT = OFF_OEX + 512;
constexpr int OFF_RED = OFF_STAT + 80;
constexpr int OFF_HS = OFF_RED + 96;
constexpr int OFF_B2 = OFF_HS + 320;
constexpr int SMEM_BYTES = OFF_B2 + 1280;

static_assert(SMEM_BYTES <= 232448, "smem");
constexpr int NREP = 4;
constexpr unsigned SPIN_LIMIT = 1u << 24;

__device__ unsigned int g_ctr;
__device__ float g_acc[4][NREP][D_MODEL];
__device__ uint4 g_ml[2][NCTA];

#define TS(i) do {} while (0)
#define TS2(i) do {} while (0)

struct Params {
    const bf16* x; const bf16* kc; const bf16* vc; const bf16* wq; const bf16* wo;
    const bf16* w1; const bf16* b1; const bf16* w2; const bf16* b2; bf16* out;
};

__device__ __forceinline__ float bf16r(float x) { return __bfloat162float(__float2bfloat16_rn(x)); }
__device__ __forceinline__ float bflo(uint32_t u) { return __uint_as_float(u << 16); }
__device__ __forceinline__ float bfhi(uint32_t u) { return __uint_as_float(u & 0xffff0000u); }

__device__ __forceinline__ uint32_t smem_u32(const void* p) { return (uint32_t)__cvta_generic_to_shared(p); }

__device__ __forceinline__ void mbar_init(uint32_t bar, uint32_t cnt) {
    asm volatile("mbarrier.init.shared::cta.b64 [%0], %1;" :: "r"(bar), "r"(cnt) : "memory");
}
__device__ __forceinline__ void mbar_expect_tx(uint32_t bar, uint32_t bytes) {
    asm volatile("mbarrier.arrive.expect_tx.shared::cta.b64 _, [%0], %1;" :: "r"(bar), "r"(bytes) : "memory");
}
__device__ __forceinline__ void mbar_wait(uint32_t bar, uint32_t parity) {
    unsigned it = 0;
    while (true) {
        uint32_t ok;
        asm volatile("{\n\t.reg .pred p;\n\tmbarrier.try_wait.parity.shared::cta.b64 p, [%1], %2;\n\tselp.u32 %0, 1, 0, p;\n\t}"
                     : "=r"(ok) : "r"(bar), "r"(parity) : "memory");
        if (ok) break;
        if (++it > SPIN_LIMIT) __trap();
    }
}
__device__ __forceinline__ void bulk_g2s(uint32_t dst, const void* src, uint32_t bytes, uint32_t bar) {
    asm volatile("cp.async.bulk.shared::cluster.global.mbarrier::complete_tx::bytes [%0], [%1], %2, [%3];"
                 :: "r"(dst), "l"(src), "r"(bytes), "r"(bar) : "memory");
}
__device__ __forceinline__ void bulk_g2s_hint(uint32_t dst, const void* src, uint32_t bytes, uint32_t bar, uint64_t pol) {
    asm volatile("cp.async.bulk.shared::cluster.global.mbarrier::complete_tx::bytes.L2::cache_hint [%0], [%1], %2, [%3], %4;"
                 :: "r"(dst), "l"(src), "r"(bytes), "r"(bar), "l"(pol) : "memory");
}
__device__ __forceinline__ void tma_2d_hint(uint32_t dst, const CUtensorMap* tm, int c0, int c1, uint32_t bar, uint64_t pol) {
    asm volatile("cp.async.bulk.tensor.2d.shared::cluster.global.mbarrier::complete_tx::bytes.L2::cache_hint [%0], [%1, {%3, %4}], [%2], %5;"
                 :: "r"(dst), "l"(tm), "r"(bar), "r"(c0), "r"(c1), "l"(pol) : "memory");
}
__device__ __forceinline__ void bulk_prefetch_l2(const void* src, uint32_t bytes) {
    asm volatile("cp.async.bulk.prefetch.L2.global [%0], %1;" :: "l"(src), "r"(bytes) : "memory");
}
__device__ __forceinline__ void bulk_prefetch_l2_hint(const void* src, uint32_t bytes, uint64_t pol) {
    asm volatile("cp.async.bulk.prefetch.L2.global.L2::cache_hint [%0], %1, %2;" :: "l"(src), "r"(bytes), "l"(pol) : "memory");
}
__device__ __forceinline__ float ex2(float x) { float y; asm("ex2.approx.ftz.f32 %0, %1;" : "=f"(y) : "f"(x)); return y; }
__device__ __forceinline__ void cp_async16_hint(uint32_t dst, const void* src, uint64_t pol) {
    asm volatile("cp.async.cg.shared.global.L2::cache_hint [%0], [%1], 16, %2;" :: "r"(dst), "l"(src), "l"(pol) : "memory");
}
__device__ __forceinline__ void cp_async_wait_all() { asm volatile("cp.async.wait_all;" ::: "memory"); }
__device__ __forceinline__ void cp_async_commit() { asm volatile("cp.async.commit_group;" ::: "memory"); }
template <int N> __device__ __forceinline__ void cp_async_wait_group() { asm volatile("cp.async.wait_group %0;" :: "n"(N) : "memory"); }

__device__ __forceinline__ void ldg128_hint(uint32_t (&r)[4], const void* p, uint64_t pol) {
    asm volatile("ld.global.nc.L1::no_allocate.L2::cache_hint.v4.u32 {%0,%1,%2,%3}, [%4], %5;"
                 : "=r"(r[0]), "=r"(r[1]), "=r"(r[2]), "=r"(r[3]) : "l"(p), "l"(pol));
}
__device__ __forceinline__ void ldg128(uint32_t (&r)[4], const void* p) {
    asm volatile("ld.global.nc.v4.u32 {%0,%1,%2,%3}, [%4];"
                 : "=r"(r[0]), "=r"(r[1]), "=r"(r[2]), "=r"(r[3]) : "l"(p));
}
__device__ __forceinline__ void mma16816(float (&c)[4], uint32_t a0, uint32_t a1, uint32_t a2, uint32_t a3,
                                         uint32_t b0, uint32_t b1) {
    asm volatile("mma.sync.aligned.m16n8k16.row.col.f32.bf16.bf16.f32 {%0,%1,%2,%3}, {%4,%5,%6,%7}, {%8,%9}, {%0,%1,%2,%3};"
                 : "+f"(c[0]), "+f"(c[1]), "+f"(c[2]), "+f"(c[3])
                 : "r"(a0), "r"(a1), "r"(a2), "r"(a3), "r"(b0), "r"(b1));
}
__device__ __forceinline__ void ldmatrix4(uint32_t (&r)[4], uint32_t addr) {
    asm volatile("ldmatrix.sync.aligned.m8n8.x4.shared.b16 {%0,%1,%2,%3}, [%4];"
                 : "=r"(r[0]), "=r"(r[1]), "=r"(r[2]), "=r"(r[3]) : "r"(addr) : "memory");
}
__device__ __forceinline__ void red_add_v4(float* p, float a, float b, float c, float d) {
    asm volatile("red.global.add.v4.f32 [%0], {%1,%2,%3,%4};" :: "l"(p), "f"(a), "f"(b), "f"(c), "f"(d) : "memory");
}
__device__ __forceinline__ unsigned ld_acquire(const unsigned* p) {
    unsigned v; asm volatile("ld.acquire.gpu.global.u32 %0, [%1];" : "=r"(v) : "l"(p) : "memory"); return v;
}
__device__ __forceinline__ void st_release(unsigned* p, unsigned v) {
    asm volatile("st.release.gpu.global.u32 [%0], %1;" :: "l"(p), "r"(v) : "memory");
}
__device__ __forceinline__ void cluster_sync_all() {
    asm volatile("barrier.cluster.arrive.release.aligned;\n\tbarrier.cluster.wait.acquire.aligned;" ::: "memory");
}
__device__ __forceinline__ uint32_t mapa(uint32_t addr, uint32_t rank) {
    uint32_t r; asm volatile("mapa.shared::cluster.u32 %0, %1, %2;" : "=r"(r) : "r"(addr), "r"(rank)); return r;
}
__device__ __forceinline__ void st_cluster_f32(uint32_t addr, float v) {
    asm volatile("st.shared::cluster.f32 [%0], %1;" :: "r"(addr), "f"(v) : "memory");
}
__device__ __forceinline__ void st_cluster_u16(uint32_t addr, uint16_t v) {
    asm volatile("st.shared::cluster.u16 [%0], %1;" :: "r"(addr), "h"(v) : "memory");
}
__device__ __forceinline__ float warp_sum(float v) {
#pragma unroll
    for (int o = 16; o > 0; o >>= 1) v += __shfl_xor_sync(0xffffffffu, v, o);
    return v;
}

__device__ __forceinline__ void grid_barrier(unsigned target) {
    __syncthreads();
    if (threadIdx.x == 0) {
        __threadfence();
        atomicAdd(&g_ctr, 1u);
        unsigned it = 0;
        while ((int)(ld_acquire(&g_ctr) - target) < 0) { if (++it > SPIN_LIMIT) __trap(); }
    }
    __syncthreads();
}

constexpr float LOG2E = 1.4426950408889634f;

__device__ __forceinline__ void ldmatrix4t(uint32_t (&r)[4], uint32_t addr) {
    asm volatile("ldmatrix.sync.aligned.m8n8.x4.trans.shared.b16 {%0,%1,%2,%3}, [%4];"
                 : "=r"(r[0]), "=r"(r[1]), "=r"(r[2]), "=r"(r[3]) : "r"(addr) : "memory");
}
__device__ __forceinline__ void red_add(float* p, float a) {
    asm volatile("red.global.add.f32 [%0], %1;" :: "l"(p), "f"(a) : "memory");
}
__device__ __forceinline__ uint32_t pack_bf16(float lo, float hi) {
    uint32_t r; asm("cvt.rn.bf16x2.f32 %0, %1, %2;" : "=r"(r) : "f"(hi), "f"(lo)); return r;
}

__global__ void __launch_bounds__(NT, 1) fused_kernel(const Params P, const __grid_constant__ CUtensorMap tm_wq,
                                                        const __grid_constant__ CUtensorMap tm_wo) {
    extern __shared__ __align__(1024) unsigned char sm[];
    const int tid = threadIdx.x, lane = tid & 31, w = tid >> 5;
    const int g = lane >> 2, t = lane & 3;
    const int b = blockIdx.x, h = b >> 2, c = b & 3, r = b & 1;
    const uint32_t sbase = smem_u32(sm);
    bf16* xs = reinterpret_cast<bf16*>(sm + OFF_XS);
    bf16* xn = reinterpret_cast<bf16*>(sm + OFF_XN);
    bf16* b2s = reinterpret_cast<bf16*>(sm + OFF_B2);
    float* oscr = reinterpret_cast<float*>(sm + OFF_O);
    bf16* qs = reinterpret_cast<bf16*>(sm + OFF_Q);
    float* oex = reinterpret_cast<float*>(sm + OFF_OEX);
    float* stat = reinterpret_cast<float*>(sm + OFF_STAT);
    float* red = reinterpret_cast<float*>(sm + OFF_RED);
    bf16* hs = reinterpret_cast<bf16*>(sm + OFF_HS);
    volatile unsigned* s_flag = reinterpret_cast<volatile unsigned*>(sm + OFF_STAT + 64);
    const uint32_t bar_stage = sbase + OFF_STAT + 72;

    TS(0);
    if (tid < D_MODEL / 8) *reinterpret_cast<uint4*>(xs + tid * 8) = __ldg(reinterpret_cast<const uint4*>(P.x) + tid);
    else if (tid < D_MODEL / 4) *reinterpret_cast<uint4*>(b2s + (tid - 80) * 8) = __ldg(reinterpret_cast<const uint4*>(P.b2) + (tid - 80));
    else if (tid < 162) { if (b < MLP_CTAS) *reinterpret_cast<uint4*>(hs + 16 + (tid - 160) * 8) = __ldg(reinterpret_cast<const uint4*>(P.b1 + b * MLP_UNITS) + (tid - 160)); }
    else if (tid == 192) s_flag[0] = ld_acquire(&g_ctr) >> 9;
    uint64_t pol_first;
    asm volatile("createpolicy.fractional.L2::evict_first.b64 %0, 1.0;" : "=l"(pol_first));

    const size_t kv_off = (size_t)(h * SEQ + c * 1024 + w * 128) * DH;
    if (tid == 224) {
        mbar_init(bar_stage, 1);
        asm volatile("fence.mbarrier_init.release.cluster;" ::: "memory");
        asm volatile("fence.proxy.async.shared::cta;" ::: "memory");
        mbar_expect_tx(bar_stage, 81920);
#pragma unroll
        for (int i = 0; i < 5; i++) tma_2d_hint(sbase + OFF_STAGE + i * 16384, &tm_wq, h * DH + r * 64, i * 128, bar_stage, pol_first);
    }
    const uint32_t kb = sbase + OFF_K + w * (KSM_TILES * 16 * 256);
    {
        const bf16* kq = P.kc + kv_off + KREG_TILES * 16 * DH;
#pragma unroll 1
        for (int it = 0; it < KSM_TILES * 8; it++) {
            const int idx = it * 32 + lane;
            const int row = idx >> 4, ch = idx & 15;
            cp_async16_hint(kb + row * 256 + ((ch ^ (row & 7)) << 4), kq + row * DH + ch * 8, pol_first);
        }
    }
    cp_async_commit();
    if (b < MLP_CTAS) {
#pragma unroll 1
        for (int idx = tid; idx < 2 * D_MODEL; idx += NT) {
            const int row = idx >> 1, hf = idx & 1;
            cp_async16_hint(sbase + OFF_W1 + row * 32 + hf * 16, P.w1 + (size_t)row * FF + b * MLP_UNITS + hf * 8, pol_first);
            const int r2 = idx / 80, ch = idx - r2 * 80;
            cp_async16_hint(sbase + OFF_W2 + r2 * 1280 + ((ch ^ (r2 & 7)) << 4), P.w2 + (size_t)(b * MLP_UNITS) * D_MODEL + idx * 8, pol_first);
        }
    }
    cp_async_commit();
    if (b == 1) for (int e = tid; e < 3 * NREP * D_MODEL; e += NT) (&g_acc[1][0][0])[e] = 0.f;
    uint32_t kreg[KREG_TILES][2][4][4];
    __syncthreads();
    const unsigned epoch = s_flag[0];
    const unsigned base = epoch << 9;

#pragma unroll 1
    for (int s = 0; s < 4; s++) {
        {
            float v[4] = {0.f, 0.f, 0.f, 0.f};
            if (tid < D_MODEL / 4) {
                const uint2 xr = *reinterpret_cast<const uint2*>(xs + tid * 4);
                v[0] = bflo(xr.x); v[1] = bfhi(xr.x); v[2] = bflo(xr.y); v[3] = bfhi(xr.y);
                if (s != 0) {
                    float4 a = __ldcg(reinterpret_cast<const float4*>(&g_acc[s - 1][0][0]) + tid);
#pragma unroll
                    for (int i = 1; i < NREP; i++) {
                        const float4 a2 = __ldcg(reinterpret_cast<const float4*>(&g_acc[s - 1][i][0]) + tid);
                        a.x += a2.x; a.y += a2.y; a.z += a2.z; a.w += a2.w;
                    }
                    a.x = bf16r(a.x); a.y = bf16r(a.y); a.z = bf16r(a.z); a.w = bf16r(a.w);
                    if (s == 2) {
                        const uint2 br = *reinterpret_cast<const uint2*>(b2s + tid * 4);
                        a.x = bf16r(a.x + bflo(br.x)); a.y = bf16r(a.y + bfhi(br.x));
                        a.z = bf16r(a.z + bflo(br.y)); a.w = bf16r(a.w + bfhi(br.y));
                    }
                    v[0] = bf16r(v[0] + a.x); v[1] = bf16r(v[1] + a.y); v[2] = bf16r(v[2] + a.z); v[3] = bf16r(v[3] + a.w);
                    *reinterpret_cast<uint2*>(xs + tid * 4) = make_uint2(pack_bf16(v[0], v[1]), pack_bf16(v[2], v[3]));
                }
            }
            if (s == 2 && b == 0) {
                for (int e = tid; e < NREP * D_MODEL; e += NT) (&g_acc[0][0][0])[e] = 0.f;
            }
#pragma unroll 1
            for (int rep = 0; rep <= (s & 1); rep++) {
                float mean = 0.25f * ((v[0] + v[1]) + (v[2] + v[3]));
                float m2 = (v[0] - mean) * (v[0] - mean) + (v[1] - mean) * (v[1] - mean) +
                           (v[2] - mean) * (v[2] - mean) + (v[3] - mean) * (v[3] - mean);
                float hn = 2.f;
#pragma unroll
                for (int o = 1; o < 32; o <<= 1) {
                    const float mo = __shfl_xor_sync(0xffffffffu, mean, o);
                    const float qo = __shfl_xor_sync(0xffffffffu, m2, o);
                    const float d = mo - mean;
                    m2 = m2 + qo + d * d * hn;
                    mean = 0.5f * (mean + mo);
                    hn *= 2.f;
                }
                float* rd = red + rep * 12;
                if (lane == 0 && w < 5) { rd[2 * w] = mean; rd[2 * w + 1] = m2; }
                __syncthreads();
                float gm = 0.f, gq = 0.f;
#pragma unroll
                for (int i = 0; i < 5; i++) { gm += rd[2 * i]; gq += rd[2 * i + 1]; }
                gm *= 0.2f;
#pragma unroll
                for (int i = 0; i < 5; i++) { const float d = rd[2 * i] - gm; gq += 128.f * d * d; }
                const float mb = bf16r(gm);
                const float den = bf16r(sqrtf(bf16r(bf16r(gq * (1.0f / D_MODEL)) + 1e-5f)));
#pragma unroll
                for (int i = 0; i < 4; i++) v[i] = bf16r(__fdividef(bf16r(v[i] - mb), den));
            }
            if (tid < D_MODEL / 4)
                *reinterpret_cast<uint2*>(xn + tid * 4) = make_uint2(pack_bf16(v[0], v[1]), pack_bf16(v[2], v[3]));
        }
        if (s == 1) cp_async_wait_all();
        __syncthreads();
        TS(1 + s * 6);
        float* acc = &g_acc[s][b & (NREP - 1)][0];

        if (!(s & 1)) {
            const int pass = s >> 1;
            mbar_wait(bar_stage, 0);
            {
                float cq[4][4];
#pragma unroll
                for (int i = 0; i < 4; i++) { cq[i][0] = cq[i][1] = cq[i][2] = cq[i][3] = 0.f; }
#pragma unroll
                for (int k5 = 0; k5 < 5; k5++) {
                    const int ks = w * 5 + k5;
                    const uint32_t b0 = *reinterpret_cast<const uint32_t*>(xn + ks * 16 + 2 * t);
                    const uint32_t b1 = *reinterpret_cast<const uint32_t*>(xn + ks * 16 + 2 * t + 8);
                    const int krow = ks * 16 + (lane & 7) + ((lane >> 4) & 1) * 8;
#pragma unroll
                    for (int mt = 0; mt < 4; mt++) {
                        uint32_t a[4];
                        ldmatrix4t(a, sbase + OFF_STAGE + krow * 128 + (((2 * mt + ((lane >> 3) & 1)) ^ (lane & 7)) << 4));
                        mma16816(cq[mt], a[0], a[1], a[2], a[3], b0, b1);
                    }
                }
                if (t == 0) {
#pragma unroll
                    for (int mt = 0; mt < 4; mt++) { oscr[w * 64 + mt * 16 + g] = cq[mt][0]; oscr[w * 64 + mt * 16 + 8 + g] = cq[mt][2]; }
                }
            }
            TS2(1);
            __syncthreads();
            if (tid < 64) {
                float sum = 0.f;
#pragma unroll
                for (int i = 0; i < 8; i++) sum += oscr[i * 64 + tid];
                const bf16 qv = __float2bfloat16_rn(sum);
                qs[r * 64 + tid] = qv;
                st_cluster_u16(mapa(sbase + OFF_Q + (r * 64 + tid) * 2, r ^ 1), __bfloat16_as_ushort(qv));
            }
            asm volatile("barrier.cluster.arrive.release.aligned;" ::: "memory");
            if (tid == 224) {
                mbar_expect_tx(bar_stage, 81920);
#pragma unroll 1
                for (int i = 0; i < 10; i++) tma_2d_hint(sbase + OFF_STAGE + i * 8192, &tm_wo, i * 64, h * DH + r * 64, bar_stage, pol_first);
            }
            if (s == 0) {
                const bf16* kp = P.kc + kv_off + (g * DH + t * 8);
#pragma unroll
                for (int i = 0; i < KREG_TILES; i++)
#pragma unroll
                    for (int hh = 0; hh < 2; hh++)
#pragma unroll
                        for (int j = 0; j < 4; j++)
                            ldg128_hint(kreg[i][hh][j], kp + (i * 16 + hh * 8) * DH + j * 32, pol_first);
            }
            TS2(3);
            asm volatile("barrier.cluster.wait.acquire.aligned;" ::: "memory");
            TS2(4);

            float sc[8][2];
            {
                float cacc[KREG_TILES][4];
#pragma unroll
                for (int i = 0; i < KREG_TILES; i++) { cacc[i][0] = cacc[i][1] = cacc[i][2] = cacc[i][3] = 0.f; }
#pragma unroll
                for (int j = 0; j < 4; j++) {
                    const uint4 qv = *reinterpret_cast<const uint4*>(qs + j * 32 + t * 8);
#pragma unroll
                    for (int i = 0; i < KREG_TILES; i++) {
                        mma16816(cacc[i], kreg[i][0][j][0], kreg[i][1][j][0], kreg[i][0][j][1], kreg[i][1][j][1], qv.x, qv.y);
                        mma16816(cacc[i], kreg[i][0][j][2], kreg[i][1][j][2], kreg[i][0][j][3], kreg[i][1][j][3], qv.z, qv.w);
                    }
                }
#pragma unroll
                for (int i = 0; i < KREG_TILES; i++) { sc[i][0] = cacc[i][0]; sc[i][1] = cacc[i][2]; }
            }
            {
                TS2(5);
                if (s == 0) {
                    if (lane == 0) bulk_prefetch_l2(P.vc + kv_off, 32768);
                    cp_async_wait_group<1>();
                    __syncwarp();
                }
                float cacc[KSM_TILES][4];
#pragma unroll
                for (int tt = 0; tt < KSM_TILES; tt++) { cacc[tt][0] = cacc[tt][1] = cacc[tt][2] = cacc[tt][3] = 0.f; }
                const int row0 = (lane & 7) + ((lane >> 3) & 1) * 8;
#pragma unroll 4
                for (int ks = 0; ks < 8; ks++) {
                    const uint32_t b0 = *reinterpret_cast<const uint32_t*>(qs + ks * 16 + 2 * t);
                    const uint32_t b1 = *reinterpret_cast<const uint32_t*>(qs + ks * 16 + 2 * t + 8);
                    const int ch = 2 * ks + (lane >> 4);
                    const uint32_t ad = kb + row0 * 256 + ((ch ^ (lane & 7)) << 4);
#pragma unroll
                    for (int tt = 0; tt < KSM_TILES; tt++) {
                        uint32_t a[4];
                        ldmatrix4(a, ad + tt * 4096);
                        mma16816(cacc[tt], a[0], a[1], a[2], a[3], b0, b1);
                    }
                }
#pragma unroll
                for (int tt = 0; tt < KSM_TILES; tt++) { sc[KREG_TILES + tt][0] = cacc[tt][0]; sc[KREG_TILES + tt][1] = cacc[tt][2]; }
            }
            TS2(6);
            bf16* pw = reinterpret_cast<bf16*>(sm + OFF_P + w * 256);
            {
                float s4[4];
#pragma unroll
                for (int q2 = 0; q2 < 4; q2++) {
                    const int i = q2 >> 1, k2 = q2 & 1;
                    const float v01 = (t & 1) ? sc[2 + i][k2] : sc[i][k2];
                    const float v23 = (t & 1) ? sc[6 + i][k2] : sc[4 + i][k2];
                    s4[q2] = (t & 2) ? v23 : v01;
                }
                float mx = -INFINITY;
#pragma unroll
                for (int q2 = 0; q2 < 4; q2++) {
                    s4[q2] = bf16r(bf16r(s4[q2]) * 0.08838834764831845f);
                    mx = fmaxf(mx, s4[q2]);
                }
#pragma unroll
                for (int o = 1; o < 32; o <<= 1) mx = fmaxf(mx, __shfl_xor_sync(0xffffffffu, mx, o));
                float l = 0.f;
#pragma unroll
                for (int q2 = 0; q2 < 4; q2++) {
                    const bf16 pb = __float2bfloat16_rn(ex2((s4[q2] - mx) * LOG2E));
                    l += __bfloat162float(pb);
                    pw[(2 * t + (q2 >> 1)) * 16 + (q2 & 1) * 8 + g] = pb;
                }
                l = warp_sum(l);
                if (lane == 0) { stat[2 * w] = mx; stat[2 * w + 1] = l; }
            }
            TS2(7);
            __syncthreads();
            TS(2 + s * 6);
            float m_cta = stat[0];
#pragma unroll
            for (int i = 1; i < 8; i++) m_cta = fmaxf(m_cta, stat[2 * i]);
            const float wfac = ex2((stat[2 * w] - m_cta) * LOG2E);
            if (tid == 0) {
                float l_cta = 0.f;
#pragma unroll
                for (int i = 0; i < 8; i++) l_cta += stat[2 * i + 1] * ex2((stat[2 * i] - m_cta) * LOG2E);
                asm volatile("st.relaxed.gpu.global.v4.u32 [%0], {%1,%2,%3,%4};" :: "l"(&g_ml[pass][b]),
                             "r"(__float_as_uint(m_cta)), "r"(__float_as_uint(l_cta)), "r"(epoch * 2 + pass + 1), "r"(0u) : "memory");
            }

            {
                const bf16* vbase = P.vc + kv_off + (4 * t) * DH + g * 8;
                float* ow = oscr + w * 128;
                float oacc[4][4];
#pragma unroll
                for (int i = 0; i < 4; i++) { oacc[i][0] = oacc[i][1] = oacc[i][2] = oacc[i][3] = 0.f; }
                uint32_t va[4][4], vb[4][4];
#pragma unroll
                for (int i = 0; i < 4; i++) ldg128(va[i], vbase + i * DH);
#pragma unroll 1
                for (int st = 0; st < 16; st += 2) {
                    {
                        const int s1 = st + 1;
                        const bf16* vp = vbase + (s1 & 7) * 16 * DH + (s1 >> 3) * 64;
#pragma unroll
                        for (int i = 0; i < 4; i++) ldg128(vb[i], vp + i * DH);
                    }
                    {
                        const uint2 pb = *reinterpret_cast<const uint2*>(pw + (st & 7) * 16 + 4 * t);
#pragma unroll
                        for (int e = 0; e < 4; e++)
                            mma16816(oacc[e], __byte_perm(va[0][e], va[1][e], 0x5410), __byte_perm(va[0][e], va[1][e], 0x7632),
                                     __byte_perm(va[2][e], va[3][e], 0x5410), __byte_perm(va[2][e], va[3][e], 0x7632), pb.x, pb.y);
                    }
                    if (st + 2 < 16) {
                        const int s2 = st + 2;
                        const bf16* vp = vbase + (s2 & 7) * 16 * DH + (s2 >> 3) * 64;
#pragma unroll
                        for (int i = 0; i < 4; i++) ldg128(va[i], vp + i * DH);
                    }
                    {
                        const uint2 pb = *reinterpret_cast<const uint2*>(pw + ((st + 1) & 7) * 16 + 4 * t);
#pragma unroll
                        for (int e = 0; e < 4; e++)
                            mma16816(oacc[e], __byte_perm(vb[0][e], vb[1][e], 0x5410), __byte_perm(vb[0][e], vb[1][e], 0x7632),
                                     __byte_perm(vb[2][e], vb[3][e], 0x5410), __byte_perm(vb[2][e], vb[3][e], 0x7632), pb.x, pb.y);
                    }
                    if ((st & 7) == 6) {
                        if (t == 0) {
                            float* o2 = ow + (st >> 3) * 64 + g * 8;
                            *reinterpret_cast<float4*>(o2) = make_float4(oacc[0][0] * wfac, oacc[0][2] * wfac, oacc[1][0] * wfac, oacc[1][2] * wfac);
                            *reinterpret_cast<float4*>(o2 + 4) = make_float4(oacc[2][0] * wfac, oacc[2][2] * wfac, oacc[3][0] * wfac, oacc[3][2] * wfac);
                        }
#pragma unroll
                        for (int i = 0; i < 4; i++) { oacc[i][0] = oacc[i][1] = oacc[i][2] = oacc[i][3] = 0.f; }
                    }
                }
            }
            __syncthreads();
            TS(3 + s * 6);
            if (tid < 128) {
                uint4 rec[4];
                {
                    unsigned it = 0;
                    const unsigned tag = epoch * 2 + pass + 1;
                    while (true) {
#pragma unroll
                        for (int i = 0; i < 4; i++)
                            asm volatile("ld.relaxed.gpu.global.v4.u32 {%0,%1,%2,%3}, [%4];"
                                         : "=r"(rec[i].x), "=r"(rec[i].y), "=r"(rec[i].z), "=r"(rec[i].w)
                                         : "l"(&g_ml[pass][(b & ~3) + i]) : "memory");
                        if (rec[0].z == tag && rec[1].z == tag && rec[2].z == tag && rec[3].z == tag) break;
                        if (++it > SPIN_LIMIT) __trap();
                    }
                }
                const float M = fmaxf(fmaxf(__uint_as_float(rec[0].x), __uint_as_float(rec[1].x)),
                                      fmaxf(__uint_as_float(rec[2].x), __uint_as_float(rec[3].x)));
                float L = 0.f;
#pragma unroll
                for (int i = 0; i < 4; i++) L += __uint_as_float(rec[i].y) * ex2((__uint_as_float(rec[i].x) - M) * LOG2E);
                const float scale = __fdividef(ex2((m_cta - M) * LOG2E), L);
                float sum = 0.f;
#pragma unroll
                for (int i = 0; i < 8; i++) sum += oscr[i * 128 + tid];
                st_cluster_f32(mapa(sbase + OFF_OEX + (r * 64 + (tid & 63)) * 4, tid >> 6), sum * scale);
            }
            TS2(8);
            cluster_sync_all();
            TS2(9);
            if (tid < 64) {
                const float o = oex[tid] + oex[64 + tid];
                const bf16 hi = __float2bfloat16_rn(o);
                hs[32 + tid] = hi;
                hs[96 + tid] = __float2bfloat16_rn(o - __bfloat162float(hi));
            }
            mbar_wait(bar_stage, 1);
            __syncthreads();
            TS(4 + s * 6);
            {
                float co[5][4];
#pragma unroll
                for (int i = 0; i < 5; i++) { co[i][0] = co[i][1] = co[i][2] = co[i][3] = 0.f; }
#pragma unroll 1
                for (int ks = 0; ks < 4; ks++) {
                    uint32_t b0 = 0, b1 = 0;
                    if (g < 2) {
                        b0 = *reinterpret_cast<const uint32_t*>(hs + 32 + g * 64 + ks * 16 + 2 * t);
                        b1 = *reinterpret_cast<const uint32_t*>(hs + 32 + g * 64 + ks * 16 + 2 * t + 8);
                    }
                    const int krow = ks * 16 + (lane & 7) + ((lane >> 4) & 1) * 8;
#pragma unroll
                    for (int i = 0; i < 5; i++) {
                        const int ch = 2 * (w * 5 + i) + ((lane >> 3) & 1);
                        uint32_t a[4];
                        ldmatrix4t(a, sbase + OFF_STAGE + (ch >> 3) * 8192 + krow * 128 + (((ch ^ lane) & 7) << 4));
                        mma16816(co[i], a[0], a[1], a[2], a[3], b0, b1);
                    }
                }
                if (t == 0) {
#pragma unroll
                    for (int i = 0; i < 5; i++) {
                        red_add(acc + (w * 5 + i) * 16 + g, co[i][0] + co[i][1]);
                        red_add(acc + (w * 5 + i) * 16 + 8 + g, co[i][2] + co[i][3]);
                    }
                }
            }
            if (s == 0) {
                __syncthreads();
                if (tid == 224) {
                    mbar_expect_tx(bar_stage, 81920);
#pragma unroll 1
                    for (int i = 0; i < 5; i++) tma_2d_hint(sbase + OFF_STAGE + i * 16384, &tm_wq, h * DH + r * 64, i * 128, bar_stage, pol_first);
                }
            }
        } else if (b < MLP_CTAS) {
            {
                float ch4[4] = {0.f, 0.f, 0.f, 0.f};
#pragma unroll
                for (int k5 = 0; k5 < 5; k5++) {
                    const int ks = w * 5 + k5;
                    const uint32_t b0 = *reinterpret_cast<const uint32_t*>(xn + ks * 16 + 2 * t);
                    const uint32_t b1 = *reinterpret_cast<const uint32_t*>(xn + ks * 16 + 2 * t + 8);
                    const int krow = ks * 16 + (lane & 7) + ((lane >> 4) & 1) * 8;
                    uint32_t a[4];
                    ldmatrix4t(a, sbase + OFF_W1 + krow * 32 + ((lane >> 3) & 1) * 16);
                    mma16816(ch4, a[0], a[1], a[2], a[3], b0, b1);
                }
                if (t == 0) { oscr[w * 16 + g] = ch4[0]; oscr[w * 16 + 8 + g] = ch4[2]; }
            }
            __syncthreads();
            if (tid < 16) {
                float sum = 0.f;
#pragma unroll
                for (int i = 0; i < 8; i++) sum += oscr[i * 16 + tid];
                const float u = bf16r(bf16r(sum) + __bfloat162float(hs[16 + tid]));
                const float inner = 0.7978845608028654f * (u + 0.044715f * u * u * u);
                hs[tid] = __float2bfloat16_rn(0.5f * u * (1.0f + tanhf(inner)));
            }
            __syncthreads();
            {
                const uint32_t b0 = *reinterpret_cast<const uint32_t*>(hs + 2 * t);
                const uint32_t b1 = *reinterpret_cast<const uint32_t*>(hs + 2 * t + 8);
                const int krow = (lane & 7) + ((lane >> 4) & 1) * 8;
#pragma unroll
                for (int i = 0; i < 5; i++) {
                    const int ch = 2 * (w * 5 + i) + ((lane >> 3) & 1);
                    uint32_t a[4];
                    float co[4] = {0.f, 0.f, 0.f, 0.f};
                    ldmatrix4t(a, sbase + OFF_W2 + krow * 1280 + ((ch ^ (lane & 7)) << 4));
                    mma16816(co, a[0], a[1], a[2], a[3], b0, b1);
                    if (t == 0) {
                        red_add(acc + (w * 5 + i) * 16 + g, co[0]);
                        red_add(acc + (w * 5 + i) * 16 + 8 + g, co[2]);
                    }
                }
            }
        }
        TS(5 + s * 6);
        if (s < 3) grid_barrier(base + NCTA * (s + 1));
        TS(6 + s * 6);
    }
    __syncthreads();
    if (tid == 0) {
        __threadfence();
        const unsigned old = atomicAdd(&g_ctr, 1u);
        s_flag[1] = (old == base + 4 * NCTA - 1) ? 1u : 0u;
        __threadfence();
    }
    __syncthreads();
    if (s_flag[1]) {
        for (int e = tid; e < D_MODEL; e += NT) {
            float a = 0.f;
#pragma unroll
            for (int i = 0; i < NREP; i++) a += __ldcg(&g_acc[3][i][e]);
            const float o = bf16r(bf16r(a) + __bfloat162float(b2s[e]));
            P.out[e] = __float2bfloat16_rn(__bfloat162float(xs[e]) + o);
        }
    }
    TS(25);
}

}

extern "C" void kernel_launch(void* const* d_in, const int* in_sizes, int n_in,
                              void* d_out, int out_size) {
    Params P;
    P.x = (const bf16*)d_in[0];
    P.kc = (const bf16*)d_in[1];
    P.vc = (const bf16*)d_in[2];
    P.wq = (const bf16*)d_in[3];
    P.wo = (const bf16*)d_in[4];
    P.w1 = (const bf16*)d_in[6];
    P.b1 = (const bf16*)d_in[7];
    P.w2 = (const bf16*)d_in[8];
    P.b2 = (const bf16*)d_in[9];
    P.out = (bf16*)d_out;

    cudaFuncSetAttribute(fused_kernel, cudaFuncAttributeMaxDynamicSharedMemorySize, SMEM_BYTES);

    typedef CUresult (*EncodeFn)(CUtensorMap*, CUtensorMapDataType, cuuint32_t, void*, const cuuint64_t*, const cuuint64_t*,
                                 const cuuint32_t*, const cuuint32_t*, CUtensorMapInterleave, CUtensorMapSwizzle,
                                 CUtensorMapL2promotion, CUtensorMapFloatOOBfill);
    void* fn = nullptr;
    cudaDriverEntryPointQueryResult qres;
    cudaGetDriverEntryPoint("cuTensorMapEncodeTiled", &fn, cudaEnableDefault, &qres);
    EncodeFn encode = (EncodeFn)fn;
    CUtensorMap tm_wq, tm_wo;
    {
        cuuint64_t dims[2] = {(cuuint64_t)(NHEAD * DH), (cuuint64_t)D_MODEL};
        cuuint64_t strides[1] = {(cuuint64_t)(NHEAD * DH * 2)};
        cuuint32_t box[2] = {64, 128};
        cuuint32_t es[2] = {1, 1};
        encode(&tm_wq, CU_TENSOR_MAP_DATA_TYPE_BFLOAT16, 2, (void*)P.wq, dims, strides, box, es, CU_TENSOR_MAP_INTERLEAVE_NONE,
               CU_TENSOR_MAP_SWIZZLE_128B, CU_TENSOR_MAP_L2_PROMOTION_NONE, CU_TENSOR_MAP_FLOAT_OOB_FILL_NONE);
    }
    {
        cuuint64_t dims[2] = {(cuuint64_t)D_MODEL, (cuuint64_t)(NHEAD * DH)};
        cuuint64_t strides[1] = {(cuuint64_t)(D_MODEL * 2)};
        cuuint32_t box[2] = {64, 64};
        cuuint32_t es[2] = {1, 1};
        encode(&tm_wo, CU_TENSOR_MAP_DATA_TYPE_BFLOAT16, 2, (void*)P.wo, dims, strides, box, es, CU_TENSOR_MAP_INTERLEAVE_NONE,
               CU_TENSOR_MAP_SWIZZLE_128B, CU_TENSOR_MAP_L2_PROMOTION_NONE, CU_TENSOR_MAP_FLOAT_OOB_FILL_NONE);
    }

    cudaLaunchConfig_t cfg = {};
    cfg.gridDim = dim3(NCTA);
    cfg.blockDim = dim3(NT);
    cfg.dynamicSmemBytes = SMEM_BYTES;
    cfg.stream = cudaStreamPerThread;
    cudaLaunchAttribute at[2];
    at[0].id = cudaLaunchAttributeClusterDimension;
    at[0].val.clusterDim.x = 2; at[0].val.clusterDim.y = 1; at[0].val.clusterDim.z = 1;
    at[1].id = cudaLaunchAttributeCooperative;
    at[1].val.cooperative = 1;
    cfg.attrs = at;
    cfg.numAttrs = 2;
    cudaLaunchKernelEx(&cfg, fused_kernel, P, tm_wq, tm_wo);
}
```

```cpp
#include <cuda_runtime.h>
#include <cuda.h>
#include <cuda_bf16.h>
#include <stdint.h>

typedef __nv_bfloat16 bf16;

namespace {

constexpr int D_MODEL = 640;
constexpr int NHEAD = 32;
constexpr int SEQ = 4096;
constexpr int DH = 128;
constexpr int FF = 1728;
constexpr int NCTA = 128;
constexpr int NT = 256;
constexpr int KREG_TILES = 5;
constexpr int KSM_TILES = 3;
constexpr int MLP_UNITS = 16;
constexpr int MLP_CTAS = FF / MLP_UNITS;

constexpr int OFF_STAGE = 0;
constexpr int OFF_W2 = 81920;
constexpr int OFF_W1 = OFF_W2 + 20480;
constexpr int OFF_K = OFF_W1 + 20480;
constexpr int OFF_XS = OFF_K + 98304;
constexpr int OFF_XN = OFF_XS + 1280;
constexpr int OFF_O = OFF_XN + 1280;
constexpr int OFF_P = OFF_O + 4096;
constexpr int OFF_Q = OFF_P + 2048;
constexpr int OFF_OEX = OFF_Q + 256;
constexpr int OFF_STAT = OFF_OEX + 512;
constexpr int OFF_RED = OFF_STAT + 80;
constexpr int OFF_HS = OFF_RED + 96;
constexpr int OFF_B2 = OFF_HS + 320;
constexpr int OFF_XBAR = OFF_B2 + 1280;
constexpr int SMEM_BYTES = OFF_XBAR + 16;

static_assert(SMEM_BYTES <= 232448, "smem");
constexpr int NREP = 4;
#define VPRE 0
#ifndef NVB
#define NVB 4
#endif
constexpr unsigned SPIN_LIMIT = 1u << 24;

__device__ unsigned int g_ctr;
__device__ float g_acc[4][NREP][D_MODEL];
__device__ uint4 g_ml[2][NCTA];

#define TS(i) do {} while (0)
#define TS2(i) do {} while (0)

struct Params {
    const bf16* x; const bf16* kc; const bf16* vc; const bf16* wq; const bf16* wo;
    const bf16* w1; const bf16* b1; const bf16* w2; const bf16* b2; bf16* out;
};

__device__ __forceinline__ float bf16r(float x) { return __bfloat162float(__float2bfloat16_rn(x)); }
__device__ __forceinline__ float bflo(uint32_t u) { return __uint_as_float(u << 16); }
__device__ __forceinline__ float bfhi(uint32_t u) { return __uint_as_float(u & 0xffff0000u); }

__device__ __forceinline__ uint32_t smem_u32(const void* p) { return (uint32_t)__cvta_generic_to_shared(p); }

__device__ __forceinline__ void mbar_init(uint32_t bar, uint32_t cnt) {
    asm volatile("mbarrier.init.shared::cta.b64 [%0], %1;" :: "r"(bar), "r"(cnt) : "memory");
}
__device__ __forceinline__ void mbar_expect_tx(uint32_t bar, uint32_t bytes) {
    asm volatile("mbarrier.arrive.expect_tx.shared::cta.b64 _, [%0], %1;" :: "r"(bar), "r"(bytes) : "memory");
}
__device__ __forceinline__ void mbar_wait(uint32_t bar, uint32_t parity) {
    unsigned it = 0;
    while (true) {
        uint32_t ok;
        asm volatile("{\n\t.reg .pred p;\n\tmbarrier.try_wait.parity.shared::cta.b64 p, [%1], %2;\n\tselp.u32 %0, 1, 0, p;\n\t}"
                     : "=r"(ok) : "r"(bar), "r"(parity) : "memory");
        if (ok) break;
        if (++it > SPIN_LIMIT) __trap();
    }
}
__device__ __forceinline__ void bulk_g2s(uint32_t dst, const void* src, uint32_t bytes, uint32_t bar) {
    asm volatile("cp.async.bulk.shared::cluster.global.mbarrier::complete_tx::bytes [%0], [%1], %2, [%3];"
                 :: "r"(dst), "l"(src), "r"(bytes), "r"(bar) : "memory");
}
__device__ __forceinline__ void bulk_g2s_hint(uint32_t dst, const void* src, uint32_t bytes, uint32_t bar, uint64_t pol) {
    asm volatile("cp.async.bulk.shared::cluster.global.mbarrier::complete_tx::bytes.L2::cache_hint [%0], [%1], %2, [%3], %4;"
                 :: "r"(dst), "l"(src), "r"(bytes), "r"(bar), "l"(pol) : "memory");
}
__device__ __forceinline__ void tma_2d_hint(uint32_t dst, const CUtensorMap* tm, int c0, int c1, uint32_t bar, uint64_t pol) {
    asm volatile("cp.async.bulk.tensor.2d.shared::cluster.global.mbarrier::complete_tx::bytes.L2::cache_hint [%0], [%1, {%3, %4}], [%2], %5;"
                 :: "r"(dst), "l"(tm), "r"(bar), "r"(c0), "r"(c1), "l"(pol) : "memory");
}
__device__ __forceinline__ void bulk_prefetch_l2(const void* src, uint32_t bytes) {
    asm volatile("cp.async.bulk.prefetch.L2.global [%0], %1;" :: "l"(src), "r"(bytes) : "memory");
}
__device__ __forceinline__ void bulk_prefetch_l2_hint(const void* src, uint32_t bytes, uint64_t pol) {
    asm volatile("cp.async.bulk.prefetch.L2.global.L2::cache_hint [%0], %1, %2;" :: "l"(src), "r"(bytes), "l"(pol) : "memory");
}
__device__ __forceinline__ float ex2(float x) { float y; asm("ex2.approx.ftz.f32 %0, %1;" : "=f"(y) : "f"(x)); return y; }
__device__ __forceinline__ void cp_async16_hint(uint32_t dst, const void* src, uint64_t pol) {
    asm volatile("cp.async.cg.shared.global.L2::cache_hint [%0], [%1], 16, %2;" :: "r"(dst), "l"(src), "l"(pol) : "memory");
}
__device__ __forceinline__ void cp_async_wait_all() { asm volatile("cp.async.wait_all;" ::: "memory"); }
__device__ __forceinline__ void cp_async_commit() { asm volatile("cp.async.commit_group;" ::: "memory"); }
template <int N> __device__ __forceinline__ void cp_async_wait_group() { asm volatile("cp.async.wait_group %0;" :: "n"(N) : "memory"); }

__device__ __forceinline__ void ldg128_hint(uint32_t (&r)[4], const void* p, uint64_t pol) {
    asm volatile("ld.global.nc.L1::no_allocate.L2::cache_hint.v4.u32 {%0,%1,%2,%3}, [%4], %5;"
                 : "=r"(r[0]), "=r"(r[1]), "=r"(r[2]), "=r"(r[3]) : "l"(p), "l"(pol));
}
__device__ __forceinline__ void ldg128(uint32_t (&r)[4], const void* p) {
    asm volatile("ld.global.nc.v4.u32 {%0,%1,%2,%3}, [%4];"
                 : "=r"(r[0]), "=r"(r[1]), "=r"(r[2]), "=r"(r[3]) : "l"(p));
}
__device__ __forceinline__ void mma16816(float (&c)[4], uint32_t a0, uint32_t a1, uint32_t a2, uint32_t a3,
                                         uint32_t b0, uint32_t b1) {
    asm volatile("mma.sync.aligned.m16n8k16.row.col.f32.bf16.bf16.f32 {%0,%1,%2,%3}, {%4,%5,%6,%7}, {%8,%9}, {%0,%1,%2,%3};"
                 : "+f"(c[0]), "+f"(c[1]), "+f"(c[2]), "+f"(c[3])
                 : "r"(a0), "r"(a1), "r"(a2), "r"(a3), "r"(b0), "r"(b1));
}
__device__ __forceinline__ void ldmatrix4(uint32_t (&r)[4], uint32_t addr) {
    asm volatile("ldmatrix.sync.aligned.m8n8.x4.shared.b16 {%0,%1,%2,%3}, [%4];"
                 : "=r"(r[0]), "=r"(r[1]), "=r"(r[2]), "=r"(r[3]) : "r"(addr) : "memory");
}
__device__ __forceinline__ void red_add_v4(float* p, float a, float b, float c, float d) {
    asm volatile("red.global.add.v4.f32 [%0], {%1,%2,%3,%4};" :: "l"(p), "f"(a), "f"(b), "f"(c), "f"(d) : "memory");
}
__device__ __forceinline__ unsigned ld_acquire(const unsigned* p) {
    unsigned v; asm volatile("ld.acquire.gpu.global.u32 %0, [%1];" : "=r"(v) : "l"(p) : "memory"); return v;
}
__device__ __forceinline__ void st_release(unsigned* p, unsigned v) {
    asm volatile("st.release.gpu.global.u32 [%0], %1;" :: "l"(p), "r"(v) : "memory");
}
__device__ __forceinline__ void cluster_sync_all() {
    asm volatile("barrier.cluster.arrive.release.aligned;\n\tbarrier.cluster.wait.acquire.aligned;" ::: "memory");
}
__device__ __forceinline__ uint32_t mapa(uint32_t addr, uint32_t rank) {
    uint32_t r; asm volatile("mapa.shared::cluster.u32 %0, %1, %2;" : "=r"(r) : "r"(addr), "r"(rank)); return r;
}
__device__ __forceinline__ void st_async_b32(uint32_t addr, uint32_t v, uint32_t bar) {
    asm volatile("st.async.weak.shared::cluster.mbarrier::complete_tx::bytes.b32 [%0], %1, [%2];" :: "r"(addr), "r"(v), "r"(bar) : "memory");
}
__device__ __forceinline__ void st_cluster_f32(uint32_t addr, float v) {
    asm volatile("st.shared::cluster.f32 [%0], %1;" :: "r"(addr), "f"(v) : "memory");
}
__device__ __forceinline__ void st_cluster_u16(uint32_t addr, uint16_t v) {
    asm volatile("st.shared::cluster.u16 [%0], %1;" :: "r"(addr), "h"(v) : "memory");
}
__device__ __forceinline__ float warp_sum(float v) {
#pragma unroll
    for (int o = 16; o > 0; o >>= 1) v += __shfl_xor_sync(0xffffffffu, v, o);
    return v;
}

__device__ __forceinline__ void grid_barrier(unsigned target) {
    __syncthreads();
    if (threadIdx.x == 0) {
        __threadfence();
        atomicAdd(&g_ctr, 1u);
        unsigned it = 0;
        while ((int)(ld_acquire(&g_ctr) - target) < 0) { if (++it > SPIN_LIMIT) __trap(); }
    }
    __syncthreads();
}

constexpr float LOG2E = 1.4426950408889634f;

__device__ __forceinline__ void ldmatrix4t(uint32_t (&r)[4], uint32_t addr) {
    asm volatile("ldmatrix.sync.aligned.m8n8.x4.trans.shared.b16 {%0,%1,%2,%3}, [%4];"
                 : "=r"(r[0]), "=r"(r[1]), "=r"(r[2]), "=r"(r[3]) : "r"(addr) : "memory");
}
__device__ __forceinline__ void red_add(float* p, float a) {
    asm volatile("red.global.add.f32 [%0], %1;" :: "l"(p), "f"(a) : "memory");
}
__device__ __forceinline__ uint32_t pack_bf16(float lo, float hi) {
    uint32_t r; asm("cvt.rn.bf16x2.f32 %0, %1, %2;" : "=r"(r) : "f"(hi), "f"(lo)); return r;
}

__global__ void __launch_bounds__(NT, 1) fused_kernel(const Params P, const __grid_constant__ CUtensorMap tm_wq,
                                                        const __grid_constant__ CUtensorMap tm_wo) {
    extern __shared__ __align__(1024) unsigned char sm[];
    const int tid = threadIdx.x, lane = tid & 31, w = tid >> 5;
    const int g = lane >> 2, t = lane & 3;
    const int b = blockIdx.x, h = b >> 2, c = b & 3, r = b & 1;
    const uint32_t sbase = smem_u32(sm);
    bf16* xs = reinterpret_cast<bf16*>(sm + OFF_XS);
    bf16* xn = reinterpret_cast<bf16*>(sm + OFF_XN);
    bf16* b2s = reinterpret_cast<bf16*>(sm + OFF_B2);
    float* oscr = reinterpret_cast<float*>(sm + OFF_O);
    bf16* qs = reinterpret_cast<bf16*>(sm + OFF_Q);
    float* oex = reinterpret_cast<float*>(sm + OFF_OEX);
    float* stat = reinterpret_cast<float*>(sm + OFF_STAT);
    float* red = reinterpret_cast<float*>(sm + OFF_RED);
    bf16* hs = reinterpret_cast<bf16*>(sm + OFF_HS);
    volatile unsigned* s_flag = reinterpret_cast<volatile unsigned*>(sm + OFF_STAT + 64);
    const uint32_t bar_stage = sbase + OFF_STAT + 72;

    TS(0);
    if (tid < D_MODEL / 8) *reinterpret_cast<uint4*>(xs + tid * 8) = __ldg(reinterpret_cast<const uint4*>(P.x) + tid);
    else if (tid < D_MODEL / 4) *reinterpret_cast<uint4*>(b2s + (tid - 80) * 8) = __ldg(reinterpret_cast<const uint4*>(P.b2) + (tid - 80));
    else if (tid < 162) { if (b < MLP_CTAS) *reinterpret_cast<uint4*>(hs + 16 + (tid - 160) * 8) = __ldg(reinterpret_cast<const uint4*>(P.b1 + b * MLP_UNITS) + (tid - 160)); }
    else if (tid == 192) s_flag[0] = ld_acquire(&g_ctr) >> 9;
    uint64_t pol_first;
    asm volatile("createpolicy.fractional.L2::evict_first.b64 %0, 1.0;" : "=l"(pol_first));

    const size_t kv_off = (size_t)(h * SEQ + c * 1024 + w * 128) * DH;
    if (tid == 224) {
        mbar_init(bar_stage, 1);
        mbar_init(sbase + OFF_XBAR, 1);
        mbar_init(sbase + OFF_XBAR + 8, 1);
        asm volatile("fence.mbarrier_init.release.cluster;" ::: "memory");
        asm volatile("fence.proxy.async.shared::cta;" ::: "memory");
        mbar_expect_tx(bar_stage, 81920);
#pragma unroll
        for (int i = 0; i < 5; i++) tma_2d_hint(sbase + OFF_STAGE + i * 16384, &tm_wq, h * DH + r * 64, i * 128, bar_stage, pol_first);
    }
    const uint32_t kb = sbase + OFF_K + w * (KSM_TILES * 16 * 256);
    {
        const bf16* kq = P.kc + kv_off + KREG_TILES * 16 * DH;
#pragma unroll 1
        for (int it = 0; it < KSM_TILES * 8; it++) {
            const int idx = it * 32 + lane;
            const int row = idx >> 4, ch = idx & 15;
            cp_async16_hint(kb + row * 256 + ((ch ^ (row & 7)) << 4), kq + row * DH + ch * 8, pol_first);
        }
    }
    cp_async_commit();
    if (b < MLP_CTAS) {
#pragma unroll 1
        for (int idx = tid; idx < 2 * D_MODEL; idx += NT) {
            const int row = idx >> 1, hf = idx & 1;
            cp_async16_hint(sbase + OFF_W1 + row * 32 + hf * 16, P.w1 + (size_t)row * FF + b * MLP_UNITS + hf * 8, pol_first);
            const int r2 = idx / 80, ch = idx - r2 * 80;
            cp_async16_hint(sbase + OFF_W2 + r2 * 1280 + ((ch ^ (r2 & 7)) << 4), P.w2 + (size_t)(b * MLP_UNITS) * D_MODEL + idx * 8, pol_first);
        }
    }
    cp_async_commit();
    if (b == 1) for (int e = tid; e < 3 * NREP * D_MODEL; e += NT) (&g_acc[1][0][0])[e] = 0.f;
    uint32_t kreg[KREG_TILES][2][4][4];
    __syncthreads();
    asm volatile("barrier.cluster.arrive.relaxed.aligned;" ::: "memory");
    const unsigned epoch = s_flag[0];
    const unsigned base = epoch << 9;

#pragma unroll 1
    for (int s = 0; s < 4; s++) {
        {
            float v[4] = {0.f, 0.f, 0.f, 0.f};
            if (tid < D_MODEL / 4) {
                const uint2 xr = *reinterpret_cast<const uint2*>(xs + tid * 4);
                v[0] = bflo(xr.x); v[1] = bfhi(xr.x); v[2] = bflo(xr.y); v[3] = bfhi(xr.y);
                if (s != 0) {
                    float4 a = __ldcg(reinterpret_cast<const float4*>(&g_acc[s - 1][0][0]) + tid);
#pragma unroll
                    for (int i = 1; i < NREP; i++) {
                        const float4 a2 = __ldcg(reinterpret_cast<const float4*>(&g_acc[s - 1][i][0]) + tid);
                        a.x += a2.x; a.y += a2.y; a.z += a2.z; a.w += a2.w;
                    }
                    a.x = bf16r(a.x); a.y = bf16r(a.y); a.z = bf16r(a.z); a.w = bf16r(a.w);
                    if (s == 2) {
                        const uint2 br = *reinterpret_cast<const uint2*>(b2s + tid * 4);
                        a.x = bf16r(a.x + bflo(br.x)); a.y = bf16r(a.y + bfhi(br.x));
                        a.z = bf16r(a.z + bflo(br.y)); a.w = bf16r(a.w + bfhi(br.y));
                    }
                    v[0] = bf16r(v[0] + a.x); v[1] = bf16r(v[1] + a.y); v[2] = bf16r(v[2] + a.z); v[3] = bf16r(v[3] + a.w);
                    *reinterpret_cast<uint2*>(xs + tid * 4) = make_uint2(pack_bf16(v[0], v[1]), pack_bf16(v[2], v[3]));
                }
            }
            if (s == 2 && b == 0) {
                for (int e = tid; e < NREP * D_MODEL; e += NT) (&g_acc[0][0][0])[e] = 0.f;
            }
#pragma unroll 1
            for (int rep = 0; rep <= (s & 1); rep++) {
                float mean = 0.25f * ((v[0] + v[1]) + (v[2] + v[3]));
                float m2 = (v[0] - mean) * (v[0] - mean) + (v[1] - mean) * (v[1] - mean) +
                           (v[2] - mean) * (v[2] - mean) + (v[3] - mean) * (v[3] - mean);
                float hn = 2.f;
#pragma unroll
                for (int o = 1; o < 32; o <<= 1) {
                    const float mo = __shfl_xor_sync(0xffffffffu, mean, o);
                    const float qo = __shfl_xor_sync(0xffffffffu, m2, o);
                    const float d = mo - mean;
                    m2 = m2 + qo + d * d * hn;
                    mean = 0.5f * (mean + mo);
                    hn *= 2.f;
                }
                float* rd = red + rep * 12;
                if (lane == 0 && w < 5) { rd[2 * w] = mean; rd[2 * w + 1] = m2; }
                __syncthreads();
                float gm = 0.f, gq = 0.f;
#pragma unroll
                for (int i = 0; i < 5; i++) { gm += rd[2 * i]; gq += rd[2 * i + 1]; }
                gm *= 0.2f;
#pragma unroll
                for (int i = 0; i < 5; i++) { const float d = rd[2 * i] - gm; gq += 128.f * d * d; }
                const float mb = bf16r(gm);
                const float den = bf16r(sqrtf(bf16r(bf16r(gq * (1.0f / D_MODEL)) + 1e-5f)));
#pragma unroll
                for (int i = 0; i < 4; i++) v[i] = bf16r(__fdividef(bf16r(v[i] - mb), den));
            }
            if (tid < D_MODEL / 4)
                *reinterpret_cast<uint2*>(xn + tid * 4) = make_uint2(pack_bf16(v[0], v[1]), pack_bf16(v[2], v[3]));
        }
        if (s == 1) cp_async_wait_all();
        __syncthreads();
        TS(1 + s * 6);
        TS2(0);
        float* acc = &g_acc[s][b & (NREP - 1)][0];

        if (!(s & 1)) {
            const int pass = s >> 1;
            mbar_wait(bar_stage, 0);
            {
                float cq[4][4];
#pragma unroll
                for (int i = 0; i < 4; i++) { cq[i][0] = cq[i][1] = cq[i][2] = cq[i][3] = 0.f; }
#pragma unroll
                for (int k5 = 0; k5 < 5; k5++) {
                    const int ks = w * 5 + k5;
                    const uint32_t b0 = *reinterpret_cast<const uint32_t*>(xn + ks * 16 + 2 * t);
                    const uint32_t b1 = *reinterpret_cast<const uint32_t*>(xn + ks * 16 + 2 * t + 8);
                    const int krow = ks * 16 + (lane & 7) + ((lane >> 4) & 1) * 8;
#pragma unroll
                    for (int mt = 0; mt < 4; mt++) {
                        uint32_t a[4];
                        ldmatrix4t(a, sbase + OFF_STAGE + krow * 128 + (((2 * mt + ((lane >> 3) & 1)) ^ (lane & 7)) << 4));
                        mma16816(cq[mt], a[0], a[1], a[2], a[3], b0, b1);
                    }
                }
                if (t == 0) {
#pragma unroll
                    for (int mt = 0; mt < 4; mt++) { oscr[w * 64 + mt * 16 + g] = cq[mt][0]; oscr[w * 64 + mt * 16 + 8 + g] = cq[mt][2]; }
                }
            }
            TS2(1);
            __syncthreads();
            TS2(2);
            if (s == 0) asm volatile("barrier.cluster.wait.aligned;" ::: "memory");
            if (tid < 32) {
                float s0 = 0.f, s1 = 0.f;
#pragma unroll
                for (int i = 0; i < 8; i++) { const float2 v2 = *reinterpret_cast<const float2*>(oscr + i * 64 + 2 * tid); s0 += v2.x; s1 += v2.y; }
                const uint32_t qp = pack_bf16(s0, s1);
                *reinterpret_cast<uint32_t*>(qs + r * 64 + 2 * tid) = qp;
                st_async_b32(mapa(sbase + OFF_Q + (r * 64 + 2 * tid) * 2, r ^ 1), qp, mapa(sbase + OFF_XBAR, r ^ 1));
                if (tid == 0) { mbar_expect_tx(sbase + OFF_XBAR, 128); mbar_expect_tx(sbase + OFF_XBAR + 8, 256); }
            }
            if (tid == 224) {
                mbar_expect_tx(bar_stage, 81920);
#pragma unroll 1
                for (int i = 0; i < 10; i++) tma_2d_hint(sbase + OFF_STAGE + i * 8192, &tm_wo, i * 64, h * DH + r * 64, bar_stage, pol_first);
            }
            if (s == 0) {
                const bf16* kp = P.kc + kv_off + (g * DH + t * 8);
#pragma unroll
                for (int i = 0; i < KREG_TILES; i++)
#pragma unroll
                    for (int hh = 0; hh < 2; hh++)
#pragma unroll
                        for (int j = 0; j < 4; j++)
                            ldg128_hint(kreg[i][hh][j], kp + (i * 16 + hh * 8) * DH + j * 32, pol_first);
                if (VPRE > 0 && lane == 0) bulk_prefetch_l2(P.vc + kv_off, VPRE);
            }
            TS2(3);
            __syncthreads();
            mbar_wait(sbase + OFF_XBAR, pass);
            TS2(4);

            float sc[8][2];
            {
                float cacc[KREG_TILES][4];
#pragma unroll
                for (int i = 0; i < KREG_TILES; i++) { cacc[i][0] = cacc[i][1] = cacc[i][2] = cacc[i][3] = 0.f; }
#pragma unroll
                for (int j = 0; j < 4; j++) {
                    const uint4 qv = *reinterpret_cast<const uint4*>(qs + j * 32 + t * 8);
#pragma unroll
                    for (int i = 0; i < KREG_TILES; i++) {
                        mma16816(cacc[i], kreg[i][0][j][0], kreg[i][1][j][0], kreg[i][0][j][1], kreg[i][1][j][1], qv.x, qv.y);
                        mma16816(cacc[i], kreg[i][0][j][2], kreg[i][1][j][2], kreg[i][0][j][3], kreg[i][1][j][3], qv.z, qv.w);
                    }
                }
#pragma unroll
                for (int i = 0; i < KREG_TILES; i++) { sc[i][0] = cacc[i][0]; sc[i][1] = cacc[i][2]; }
            }
            {
                TS2(5);
                if (s == 0) {
                    if (lane == 0) bulk_prefetch_l2(P.vc + kv_off + VPRE / 2, 32768 - VPRE);
                    cp_async_wait_group<1>();
                    __syncwarp();
                }
                float cacc[KSM_TILES][4];
#pragma unroll
                for (int tt = 0; tt < KSM_TILES; tt++) { cacc[tt][0] = cacc[tt][1] = cacc[tt][2] = cacc[tt][3] = 0.f; }
                const int row0 = (lane & 7) + ((lane >> 3) & 1) * 8;
#pragma unroll 4
                for (int ks = 0; ks < 8; ks++) {
                    const uint32_t b0 = *reinterpret_cast<const uint32_t*>(qs + ks * 16 + 2 * t);
                    const uint32_t b1 = *reinterpret_cast<const uint32_t*>(qs + ks * 16 + 2 * t + 8);
                    const int ch = 2 * ks + (lane >> 4);
                    const uint32_t ad = kb + row0 * 256 + ((ch ^ (lane & 7)) << 4);
#pragma unroll
                    for (int tt = 0; tt < KSM_TILES; tt++) {
                        uint32_t a[4];
                        ldmatrix4(a, ad + tt * 4096);
                        mma16816(cacc[tt], a[0], a[1], a[2], a[3], b0, b1);
                    }
                }
#pragma unroll
                for (int tt = 0; tt < KSM_TILES; tt++) { sc[KREG_TILES + tt][0] = cacc[tt][0]; sc[KREG_TILES + tt][1] = cacc[tt][2]; }
            }
            TS2(6);
            bf16* pw = reinterpret_cast<bf16*>(sm + OFF_P + w * 256);
            {
                float s4[4];
#pragma unroll
                for (int q2 = 0; q2 < 4; q2++) {
                    const int i = q2 >> 1, k2 = q2 & 1;
                    const float v01 = (t & 1) ? sc[2 + i][k2] : sc[i][k2];
                    const float v23 = (t & 1) ? sc[6 + i][k2] : sc[4 + i][k2];
                    s4[q2] = (t & 2) ? v23 : v01;
                }
                float mx = -INFINITY;
#pragma unroll
                for (int q2 = 0; q2 < 4; q2++) {
                    s4[q2] = bf16r(bf16r(s4[q2]) * 0.08838834764831845f);
                    mx = fmaxf(mx, s4[q2]);
                }
#pragma unroll
                for (int o = 1; o < 32; o <<= 1) mx = fmaxf(mx, __shfl_xor_sync(0xffffffffu, mx, o));
                float l = 0.f;
#pragma unroll
                for (int q2 = 0; q2 < 4; q2++) {
                    const bf16 pb = __float2bfloat16_rn(ex2((s4[q2] - mx) * LOG2E));
                    l += __bfloat162float(pb);
                    pw[(2 * t + (q2 >> 1)) * 16 + (q2 & 1) * 8 + g] = pb;
                }
                l = warp_sum(l);
                if (lane == 0) { stat[2 * w] = mx; stat[2 * w + 1] = l; }
            }
            TS2(7);
            __syncthreads();
            TS(2 + s * 6);
            float m_cta = stat[0];
#pragma unroll
            for (int i = 1; i < 8; i++) m_cta = fmaxf(m_cta, stat[2 * i]);
            const float wfac = ex2((stat[2 * w] - m_cta) * LOG2E);
            if (tid == 0) {
                float l_cta = 0.f;
#pragma unroll
                for (int i = 0; i < 8; i++) l_cta += stat[2 * i + 1] * ex2((stat[2 * i] - m_cta) * LOG2E);
                asm volatile("st.relaxed.gpu.global.v4.u32 [%0], {%1,%2,%3,%4};" :: "l"(&g_ml[pass][b]),
                             "r"(__float_as_uint(m_cta)), "r"(__float_as_uint(l_cta)), "r"(epoch * 2 + pass + 1), "r"(0u) : "memory");
            }

            {
                const bf16* vbase = P.vc + kv_off + (4 * t) * DH + g * 8;
                float* ow = oscr + w * 128;
                float oacc[4][4];
#pragma unroll
                for (int i = 0; i < 4; i++) { oacc[i][0] = oacc[i][1] = oacc[i][2] = oacc[i][3] = 0.f; }
                uint32_t vbuf[NVB][4][4];
#pragma unroll
                for (int u = 0; u < NVB - 1; u++)
#pragma unroll
                    for (int i = 0; i < 4; i++) ldg128(vbuf[u][i], vbase + (u * 16 + i) * DH);
#pragma unroll 1
                for (int st0 = 0; st0 < 16; st0 += NVB) {
#pragma unroll
                    for (int u = 0; u < NVB; u++) {
                        const int st = st0 + u;
                        const int nx = st + NVB - 1;
                        if (nx < 16) {
                            const bf16* vp = vbase + (nx & 7) * 16 * DH + (nx >> 3) * 64;
#pragma unroll
                            for (int i = 0; i < 4; i++) ldg128(vbuf[(u + NVB - 1) % NVB][i], vp + i * DH);
                        }
                        const uint2 pb = *reinterpret_cast<const uint2*>(pw + (st & 7) * 16 + 4 * t);
#pragma unroll
                        for (int e = 0; e < 4; e++)
                            mma16816(oacc[e], __byte_perm(vbuf[u][0][e], vbuf[u][1][e], 0x5410), __byte_perm(vbuf[u][0][e], vbuf[u][1][e], 0x7632),
                                     __byte_perm(vbuf[u][2][e], vbuf[u][3][e], 0x5410), __byte_perm(vbuf[u][2][e], vbuf[u][3][e], 0x7632), pb.x, pb.y);
                    }
                    if (((st0 + NVB) & 7) == 0) {
                        if (t == 0) {
                            float* o2 = ow + (st0 >> 3) * 64 + g * 8;
                            *reinterpret_cast<float4*>(o2) = make_float4(oacc[0][0] * wfac, oacc[0][2] * wfac, oacc[1][0] * wfac, oacc[1][2] * wfac);
                            *reinterpret_cast<float4*>(o2 + 4) = make_float4(oacc[2][0] * wfac, oacc[2][2] * wfac, oacc[3][0] * wfac, oacc[3][2] * wfac);
                        }
#pragma unroll
                        for (int i = 0; i < 4; i++) { oacc[i][0] = oacc[i][1] = oacc[i][2] = oacc[i][3] = 0.f; }
                    }
                }
            }
            __syncthreads();
            TS(3 + s * 6);
            TS2(10);
            if (tid < 128) {
                uint4 rec[4];
                {
                    unsigned it = 0;
                    const unsigned tag = epoch * 2 + pass + 1;
                    while (true) {
#pragma unroll
                        for (int i = 0; i < 4; i++)
                            asm volatile("ld.relaxed.gpu.global.v4.u32 {%0,%1,%2,%3}, [%4];"
                                         : "=r"(rec[i].x), "=r"(rec[i].y), "=r"(rec[i].z), "=r"(rec[i].w)
                                         : "l"(&g_ml[pass][(b & ~3) + i]) : "memory");
                        if (rec[0].z == tag && rec[1].z == tag && rec[2].z == tag && rec[3].z == tag) break;
                        if (++it > SPIN_LIMIT) __trap();
                    }
                }
                const float M = fmaxf(fmaxf(__uint_as_float(rec[0].x), __uint_as_float(rec[1].x)),
                                      fmaxf(__uint_as_float(rec[2].x), __uint_as_float(rec[3].x)));
                float L = 0.f;
#pragma unroll
                for (int i = 0; i < 4; i++) L += __uint_as_float(rec[i].y) * ex2((__uint_as_float(rec[i].x) - M) * LOG2E);
                const float scale = __fdividef(ex2((m_cta - M) * LOG2E), L);
                float sum = 0.f;
#pragma unroll
                for (int i = 0; i < 8; i++) sum += oscr[i * 128 + tid];
                if ((tid >> 6) == r) oex[r * 64 + (tid & 63)] = sum * scale;
                else st_async_b32(mapa(sbase + OFF_OEX + (r * 64 + (tid & 63)) * 4, r ^ 1), __float_as_uint(sum * scale), mapa(sbase + OFF_XBAR + 8, r ^ 1));
            }
            TS2(8);
            __syncthreads();
            TS2(9);
            if (tid < 64) {
                mbar_wait(sbase + OFF_XBAR + 8, pass);
                const float o = oex[tid] + oex[64 + tid];
                const bf16 hi = __float2bfloat16_rn(o);
                hs[32 + tid] = hi;
                hs[96 + tid] = __float2bfloat16_rn(o - __bfloat162float(hi));
            }
            mbar_wait(bar_stage, 1);
            __syncthreads();
            TS(4 + s * 6);
            {
                float co[5][4];
#pragma unroll
                for (int i = 0; i < 5; i++) { co[i][0] = co[i][1] = co[i][2] = co[i][3] = 0.f; }
#pragma unroll 1
                for (int ks = 0; ks < 4; ks++) {
                    uint32_t b0 = 0, b1 = 0;
                    if (g < 2) {
                        b0 = *reinterpret_cast<const uint32_t*>(hs + 32 + g * 64 + ks * 16 + 2 * t);
                        b1 = *reinterpret_cast<const uint32_t*>(hs + 32 + g * 64 + ks * 16 + 2 * t + 8);
                    }
                    const int krow = ks * 16 + (lane & 7) + ((lane >> 4) & 1) * 8;
#pragma unroll
                    for (int i = 0; i < 5; i++) {
                        const int ch = 2 * (w * 5 + i) + ((lane >> 3) & 1);
                        uint32_t a[4];
                        ldmatrix4t(a, sbase + OFF_STAGE + (ch >> 3) * 8192 + krow * 128 + (((ch ^ lane) & 7) << 4));
                        mma16816(co[i], a[0], a[1], a[2], a[3], b0, b1);
                    }
                }
                if (t == 0) {
#pragma unroll
                    for (int i = 0; i < 5; i++) {
                        red_add(acc + (w * 5 + i) * 16 + g, co[i][0] + co[i][1]);
                        red_add(acc + (w * 5 + i) * 16 + 8 + g, co[i][2] + co[i][3]);
                    }
                }
            }
            if (s == 0) {
                __syncthreads();
                if (tid == 224) {
                    mbar_expect_tx(bar_stage, 81920);
#pragma unroll 1
                    for (int i = 0; i < 5; i++) tma_2d_hint(sbase + OFF_STAGE + i * 16384, &tm_wq, h * DH + r * 64, i * 128, bar_stage, pol_first);
                }
            }
        } else if (b < MLP_CTAS) {
            {
                float ch4[4] = {0.f, 0.f, 0.f, 0.f};
#pragma unroll
                for (int k5 = 0; k5 < 5; k5++) {
                    const int ks = w * 5 + k5;
                    const uint32_t b0 = *reinterpret_cast<const uint32_t*>(xn + ks * 16 + 2 * t);
                    const uint32_t b1 = *reinterpret_cast<const uint32_t*>(xn + ks * 16 + 2 * t + 8);
                    const int krow = ks * 16 + (lane & 7) + ((lane >> 4) & 1) * 8;
                    uint32_t a[4];
                    ldmatrix4t(a, sbase + OFF_W1 + krow * 32 + ((lane >> 3) & 1) * 16);
                    mma16816(ch4, a[0], a[1], a[2], a[3], b0, b1);
                }
                if (t == 0) { oscr[w * 16 + g] = ch4[0]; oscr[w * 16 + 8 + g] = ch4[2]; }
            }
            __syncthreads();
            if (tid < 16) {
                float sum = 0.f;
#pragma unroll
                for (int i = 0; i < 8; i++) sum += oscr[i * 16 + tid];
                const float u = bf16r(bf16r(sum) + __bfloat162float(hs[16 + tid]));
                const float inner = 0.7978845608028654f * (u + 0.044715f * u * u * u);
                hs[tid] = __float2bfloat16_rn(0.5f * u * (1.0f + tanhf(inner)));
            }
            __syncthreads();
            {
                const uint32_t b0 = *reinterpret_cast<const uint32_t*>(hs + 2 * t);
                const uint32_t b1 = *reinterpret_cast<const uint32_t*>(hs + 2 * t + 8);
                const int krow = (lane & 7) + ((lane >> 4) & 1) * 8;
#pragma unroll
                for (int i = 0; i < 5; i++) {
                    const int ch = 2 * (w * 5 + i) + ((lane >> 3) & 1);
                    uint32_t a[4];
                    float co[4] = {0.f, 0.f, 0.f, 0.f};
                    ldmatrix4t(a, sbase + OFF_W2 + krow * 1280 + ((ch ^ (lane & 7)) << 4));
                    mma16816(co, a[0], a[1], a[2], a[3], b0, b1);
                    if (t == 0) {
                        red_add(acc + (w * 5 + i) * 16 + g, co[0]);
                        red_add(acc + (w * 5 + i) * 16 + 8 + g, co[2]);
                    }
                }
            }
        }
        TS(5 + s * 6);
        TS2(11);
        if (s < 3) grid_barrier(base + NCTA * (s + 1));
        TS(6 + s * 6);
    }
    __syncthreads();
    if (tid == 0) {
        __threadfence();
        const unsigned old = atomicAdd(&g_ctr, 1u);
        s_flag[1] = (old == base + 4 * NCTA - 1) ? 1u : 0u;
        __threadfence();
    }
    __syncthreads();
    if (s_flag[1]) {
        for (int e = tid; e < D_MODEL; e += NT) {
            float a = 0.f;
#pragma unroll
            for (int i = 0; i < NREP; i++) a += __ldcg(&g_acc[3][i][e]);
            const float o = bf16r(bf16r(a) + __bfloat162float(b2s[e]));
            P.out[e] = __float2bfloat16_rn(__bfloat162float(xs[e]) + o);
        }
    }
    TS(25);
}

}

extern "C" void kernel_launch(void* const* d_in, const int* in_sizes, int n_in,
                              void* d_out, int out_size) {
    Params P;
    P.x = (const bf16*)d_in[0];
    P.kc = (const bf16*)d_in[1];
    P.vc = (const bf16*)d_in[2];
    P.wq = (const bf16*)d_in[3];
    P.wo = (const bf16*)d_in[4];
    P.w1 = (const bf16*)d_in[6];
    P.b1 = (const bf16*)d_in[7];
    P.w2 = (const bf16*)d_in[8];
    P.b2 = (const bf16*)d_in[9];
    P.out = (bf16*)d_out;

    cudaFuncSetAttribute(fused_kernel, cudaFuncAttributeMaxDynamicSharedMemorySize, SMEM_BYTES);

    typedef CUresult (*EncodeFn)(CUtensorMap*, CUtensorMapDataType, cuuint32_t, void*, const cuuint64_t*, const cuuint64_t*,
                                 const cuuint32_t*, const cuuint32_t*, CUtensorMapInterleave, CUtensorMapSwizzle,
                                 CUtensorMapL2promotion, CUtensorMapFloatOOBfill);
    void* fn = nullptr;
    cudaDriverEntryPointQueryResult qres;
    cudaGetDriverEntryPoint("cuTensorMapEncodeTiled", &fn, cudaEnableDefault, &qres);
    EncodeFn encode = (EncodeFn)fn;
    CUtensorMap tm_wq, tm_wo;
    {
        cuuint64_t dims[2] = {(cuuint64_t)(NHEAD * DH), (cuuint64_t)D_MODEL};
        cuuint64_t strides[1] = {(cuuint64_t)(NHEAD * DH * 2)};
        cuuint32_t box[2] = {64, 128};
        cuuint32_t es[2] = {1, 1};
        encode(&tm_wq, CU_TENSOR_MAP_DATA_TYPE_BFLOAT16, 2, (void*)P.wq, dims, strides, box, es, CU_TENSOR_MAP_INTERLEAVE_NONE,
               CU_TENSOR_MAP_SWIZZLE_128B, CU_TENSOR_MAP_L2_PROMOTION_NONE, CU_TENSOR_MAP_FLOAT_OOB_FILL_NONE);
    }
    {
        cuuint64_t dims[2] = {(cuuint64_t)D_MODEL, (cuuint64_t)(NHEAD * DH)};
        cuuint64_t strides[1] = {(cuuint64_t)(D_MODEL * 2)};
        cuuint32_t box[2] = {64, 64};
        cuuint32_t es[2] = {1, 1};
        encode(&tm_wo, CU_TENSOR_MAP_DATA_TYPE_BFLOAT16, 2, (void*)P.wo, dims, strides, box, es, CU_TENSOR_MAP_INTERLEAVE_NONE,
               CU_TENSOR_MAP_SWIZZLE_128B, CU_TENSOR_MAP_L2_PROMOTION_NONE, CU_TENSOR_MAP_FLOAT_OOB_FILL_NONE);
    }

    cudaLaunchConfig_t cfg = {};
    cfg.gridDim = dim3(NCTA);
    cfg.blockDim = dim3(NT);
    cfg.dynamicSmemBytes = SMEM_BYTES;
    cfg.stream = cudaStreamPerThread;
    cudaLaunchAttribute at[2];
    at[0].id = cudaLaunchAttributeClusterDimension;
    at[0].val.clusterDim.x = 2; at[0].val.clusterDim.y = 1; at[0].val.clusterDim.z = 1;
    at[1].id = cudaLaunchAttributeCooperative;
    at[1].val.cooperative = 1;
    cfg.attrs = at;
    cfg.numAttrs = 2;
    cudaLaunchKernelEx(&cfg, fused_kernel, P, tm_wq, tm_wo);
}
```

```cpp
#include <cuda_runtime.h>
#include <cuda.h>
#include <cuda_bf16.h>
#include <stdint.h>

typedef __nv_bfloat16 bf16;

namespace {

constexpr int D_MODEL = 640;
constexpr int NHEAD = 32;
constexpr int SEQ = 4096;
constexpr int DH = 128;
constexpr int FF = 1728;
constexpr int NCTA = 128;
constexpr int NT = 256;
constexpr int KREG_TILES = 5;
constexpr int KSM_TILES = 3;
constexpr int MLP_UNITS = 16;
constexpr int MLP_CTAS = FF / MLP_UNITS;

constexpr int OFF_STAGE = 0;
constexpr int OFF_W2 = 81920;
constexpr int OFF_W1 = OFF_W2 + 20480;
constexpr int OFF_K = OFF_W1 + 20480;
constexpr int OFF_XS = OFF_K + 98304;
constexpr int OFF_XN = OFF_XS + 1280;
constexpr int OFF_O = OFF_XN + 1280;
constexpr int OFF_P = OFF_O + 4096;
constexpr int OFF_Q = OFF_P + 2048;
constexpr int OFF_OEX = OFF_Q + 256;
constexpr int OFF_STAT = OFF_OEX + 512;
constexpr int OFF_RED = OFF_STAT + 80;
constexpr int OFF_HS = OFF_RED + 96;
constexpr int OFF_B2 = OFF_HS + 320;
constexpr int OFF_XBAR = OFF_B2 + 1280;
constexpr int SMEM_BYTES = OFF_XBAR + 16;

static_assert(SMEM_BYTES <= 232448, "smem");
constexpr int NREP = 4;
constexpr int VL = 2;
#define VPRE 0
#ifndef NVB
#define NVB 2
#endif
constexpr unsigned SPIN_LIMIT = 1u << 24;

__device__ unsigned int g_ctr;
__device__ float g_acc[4][NREP][D_MODEL];
__device__ uint4 g_ml[2][NCTA];

#define TS(i) do {} while (0)
#define TS2(i) do {} while (0)

struct Params {
    const bf16* x; const bf16* kc; const bf16* vc; const bf16* wq; const bf16* wo;
    const bf16* w1; const bf16* b1; const bf16* w2; const bf16* b2; bf16* out;
};

__device__ __forceinline__ float bf16r(float x) { return __bfloat162float(__float2bfloat16_rn(x)); }
__device__ __forceinline__ float bflo(uint32_t u) { return __uint_as_float(u << 16); }
__device__ __forceinline__ float bfhi(uint32_t u) { return __uint_as_float(u & 0xffff0000u); }

__device__ __forceinline__ uint32_t smem_u32(const void* p) { return (uint32_t)__cvta_generic_to_shared(p); }

__device__ __forceinline__ void mbar_init(uint32_t bar, uint32_t cnt) {
    asm volatile("mbarrier.init.shared::cta.b64 [%0], %1;" :: "r"(bar), "r"(cnt) : "memory");
}
__device__ __forceinline__ void mbar_expect_tx(uint32_t bar, uint32_t bytes) {
    asm volatile("mbarrier.arrive.expect_tx.shared::cta.b64 _, [%0], %1;" :: "r"(bar), "r"(bytes) : "memory");
}
__device__ __forceinline__ void mbar_wait(uint32_t bar, uint32_t parity) {
    unsigned it = 0;
    while (true) {
        uint32_t ok;
        asm volatile("{\n\t.reg .pred p;\n\tmbarrier.try_wait.parity.shared::cta.b64 p, [%1], %2;\n\tselp.u32 %0, 1, 0, p;\n\t}"
                     : "=r"(ok) : "r"(bar), "r"(parity) : "memory");
        if (ok) break;
        if (++it > SPIN_LIMIT) __trap();
    }
}
__device__ __forceinline__ void bulk_g2s(uint32_t dst, const void* src, uint32_t bytes, uint32_t bar) {
    asm volatile("cp.async.bulk.shared::cluster.global.mbarrier::complete_tx::bytes [%0], [%1], %2, [%3];"
                 :: "r"(dst), "l"(src), "r"(bytes), "r"(bar) : "memory");
}
__device__ __forceinline__ void bulk_g2s_hint(uint32_t dst, const void* src, uint32_t bytes, uint32_t bar, uint64_t pol) {
    asm volatile("cp.async.bulk.shared::cluster.global.mbarrier::complete_tx::bytes.L2::cache_hint [%0], [%1], %2, [%3], %4;"
                 :: "r"(dst), "l"(src), "r"(bytes), "r"(bar), "l"(pol) : "memory");
}
__device__ __forceinline__ void tma_2d_hint(uint32_t dst, const CUtensorMap* tm, int c0, int c1, uint32_t bar, uint64_t pol) {
    asm volatile("cp.async.bulk.tensor.2d.shared::cluster.global.mbarrier::complete_tx::bytes.L2::cache_hint [%0], [%1, {%3, %4}], [%2], %5;"
                 :: "r"(dst), "l"(tm), "r"(bar), "r"(c0), "r"(c1), "l"(pol) : "memory");
}
__device__ __forceinline__ void bulk_prefetch_l2(const void* src, uint32_t bytes) {
    asm volatile("cp.async.bulk.prefetch.L2.global [%0], %1;" :: "l"(src), "r"(bytes) : "memory");
}
__device__ __forceinline__ void bulk_prefetch_l2_hint(const void* src, uint32_t bytes, uint64_t pol) {
    asm volatile("cp.async.bulk.prefetch.L2.global.L2::cache_hint [%0], %1, %2;" :: "l"(src), "r"(bytes), "l"(pol) : "memory");
}
__device__ __forceinline__ float ex2(float x) { float y; asm("ex2.approx.ftz.f32 %0, %1;" : "=f"(y) : "f"(x)); return y; }
__device__ __forceinline__ void cp_async16_hint(uint32_t dst, const void* src, uint64_t pol) {
    asm volatile("cp.async.cg.shared.global.L2::cache_hint [%0], [%1], 16, %2;" :: "r"(dst), "l"(src), "l"(pol) : "memory");
}
__device__ __forceinline__ void cp_async_wait_all() { asm volatile("cp.async.wait_all;" ::: "memory"); }
__device__ __forceinline__ void cp_async_commit() { asm volatile("cp.async.commit_group;" ::: "memory"); }
template <int N> __device__ __forceinline__ void cp_async_wait_group() { asm volatile("cp.async.wait_group %0;" :: "n"(N) : "memory"); }

__device__ __forceinline__ void ldg128_hint(uint32_t (&r)[4], const void* p, uint64_t pol) {
    asm volatile("ld.global.nc.L1::no_allocate.L2::cache_hint.v4.u32 {%0,%1,%2,%3}, [%4], %5;"
                 : "=r"(r[0]), "=r"(r[1]), "=r"(r[2]), "=r"(r[3]) : "l"(p), "l"(pol));
}
__device__ __forceinline__ void ldg128(uint32_t (&r)[4], const void* p) {
    asm volatile("ld.global.nc.v4.u32 {%0,%1,%2,%3}, [%4];"
                 : "=r"(r[0]), "=r"(r[1]), "=r"(r[2]), "=r"(r[3]) : "l"(p));
}
__device__ __forceinline__ void mma16816(float (&c)[4], uint32_t a0, uint32_t a1, uint32_t a2, uint32_t a3,
                                         uint32_t b0, uint32_t b1) {
    asm volatile("mma.sync.aligned.m16n8k16.row.col.f32.bf16.bf16.f32 {%0,%1,%2,%3}, {%4,%5,%6,%7}, {%8,%9}, {%0,%1,%2,%3};"
                 : "+f"(c[0]), "+f"(c[1]), "+f"(c[2]), "+f"(c[3])
                 : "r"(a0), "r"(a1), "r"(a2), "r"(a3), "r"(b0), "r"(b1));
}
__device__ __forceinline__ void ldmatrix4(uint32_t (&r)[4], uint32_t addr) {
    asm volatile("ldmatrix.sync.aligned.m8n8.x4.shared.b16 {%0,%1,%2,%3}, [%4];"
                 : "=r"(r[0]), "=r"(r[1]), "=r"(r[2]), "=r"(r[3]) : "r"(addr) : "memory");
}
__device__ __forceinline__ void red_add_v4(float* p, float a, float b, float c, float d) {
    asm volatile("red.global.add.v4.f32 [%0], {%1,%2,%3,%4};" :: "l"(p), "f"(a), "f"(b), "f"(c), "f"(d) : "memory");
}
__device__ __forceinline__ unsigned ld_acquire(const unsigned* p) {
    unsigned v; asm volatile("ld.acquire.gpu.global.u32 %0, [%1];" : "=r"(v) : "l"(p) : "memory"); return v;
}
__device__ __forceinline__ void st_release(unsigned* p, unsigned v) {
    asm volatile("st.release.gpu.global.u32 [%0], %1;" :: "l"(p), "r"(v) : "memory");
}
__device__ __forceinline__ void cluster_sync_all() {
    asm volatile("barrier.cluster.arrive.release.aligned;\n\tbarrier.cluster.wait.acquire.aligned;" ::: "memory");
}
__device__ __forceinline__ uint32_t mapa(uint32_t addr, uint32_t rank) {
    uint32_t r; asm volatile("mapa.shared::cluster.u32 %0, %1, %2;" : "=r"(r) : "r"(addr), "r"(rank)); return r;
}
__device__ __forceinline__ void st_async_b32(uint32_t addr, uint32_t v, uint32_t bar) {
    asm volatile("st.async.weak.shared::cluster.mbarrier::complete_tx::bytes.b32 [%0], %1, [%2];" :: "r"(addr), "r"(v), "r"(bar) : "memory");
}
__device__ __forceinline__ void st_cluster_f32(uint32_t addr, float v) {
    asm volatile("st.shared::cluster.f32 [%0], %1;" :: "r"(addr), "f"(v) : "memory");
}
__device__ __forceinline__ void st_cluster_u16(uint32_t addr, uint16_t v) {
    asm volatile("st.shared::cluster.u16 [%0], %1;" :: "r"(addr), "h"(v) : "memory");
}
__device__ __forceinline__ float warp_sum(float v) {
#pragma unroll
    for (int o = 16; o > 0; o >>= 1) v += __shfl_xor_sync(0xffffffffu, v, o);
    return v;
}

__device__ __forceinline__ void grid_barrier(unsigned target) {
    __syncthreads();
    if (threadIdx.x == 0) {
        __threadfence();
        atomicAdd(&g_ctr, 1u);
        unsigned it = 0;
        while ((int)(ld_acquire(&g_ctr) - target) < 0) { if (++it > SPIN_LIMIT) __trap(); }
    }
    __syncthreads();
}

constexpr float LOG2E = 1.4426950408889634f;

__device__ __forceinline__ void ldmatrix4t(uint32_t (&r)[4], uint32_t addr) {
    asm volatile("ldmatrix.sync.aligned.m8n8.x4.trans.shared.b16 {%0,%1,%2,%3}, [%4];"
                 : "=r"(r[0]), "=r"(r[1]), "=r"(r[2]), "=r"(r[3]) : "r"(addr) : "memory");
}
__device__ __forceinline__ void red_add(float* p, float a) {
    asm volatile("red.global.add.f32 [%0], %1;" :: "l"(p), "f"(a) : "memory");
}
__device__ __forceinline__ uint32_t pack_bf16(float lo, float hi) {
    uint32_t r; asm("cvt.rn.bf16x2.f32 %0, %1, %2;" : "=r"(r) : "f"(hi), "f"(lo)); return r;
}

__global__ void __launch_bounds__(NT, 1) fused_kernel(const Params P, const __grid_constant__ CUtensorMap tm_wq,
                                                        const __grid_constant__ CUtensorMap tm_wo) {
    extern __shared__ __align__(1024) unsigned char sm[];
    const int tid = threadIdx.x, lane = tid & 31, w = tid >> 5;
    const int g = lane >> 2, t = lane & 3;
    const int b = blockIdx.x, h = b >> 2, c = b & 3, r = b & 1;
    const uint32_t sbase = smem_u32(sm);
    bf16* xs = reinterpret_cast<bf16*>(sm + OFF_XS);
    bf16* xn = reinterpret_cast<bf16*>(sm + OFF_XN);
    bf16* b2s = reinterpret_cast<bf16*>(sm + OFF_B2);
    float* oscr = reinterpret_cast<float*>(sm + OFF_O);
    bf16* qs = reinterpret_cast<bf16*>(sm + OFF_Q);
    float* oex = reinterpret_cast<float*>(sm + OFF_OEX);
    float* stat = reinterpret_cast<float*>(sm + OFF_STAT);
    float* red = reinterpret_cast<float*>(sm + OFF_RED);
    bf16* hs = reinterpret_cast<bf16*>(sm + OFF_HS);
    volatile unsigned* s_flag = reinterpret_cast<volatile unsigned*>(sm + OFF_STAT + 64);
    const uint32_t bar_stage = sbase + OFF_STAT + 72;

    TS(0);
    if (tid < D_MODEL / 8) *reinterpret_cast<uint4*>(xs + tid * 8) = __ldg(reinterpret_cast<const uint4*>(P.x) + tid);
    else if (tid < D_MODEL / 4) *reinterpret_cast<uint4*>(b2s + (tid - 80) * 8) = __ldg(reinterpret_cast<const uint4*>(P.b2) + (tid - 80));
    else if (tid < 162) { if (b < MLP_CTAS) *reinterpret_cast<uint4*>(hs + 16 + (tid - 160) * 8) = __ldg(reinterpret_cast<const uint4*>(P.b1 + b * MLP_UNITS) + (tid - 160)); }
    else if (tid == 192) s_flag[0] = ld_acquire(&g_ctr) >> 9;
    uint64_t pol_first;
    asm volatile("createpolicy.fractional.L2::evict_first.b64 %0, 1.0;" : "=l"(pol_first));

    const size_t kv_off = (size_t)(h * SEQ + c * 1024 + w * 128) * DH;
    if (tid == 224) {
        mbar_init(bar_stage, 1);
        mbar_init(sbase + OFF_XBAR, 1);
        mbar_init(sbase + OFF_XBAR + 8, 1);
        asm volatile("fence.mbarrier_init.release.cluster;" ::: "memory");
        asm volatile("fence.proxy.async.shared::cta;" ::: "memory");
        mbar_expect_tx(bar_stage, 81920);
#pragma unroll
        for (int i = 0; i < 5; i++) tma_2d_hint(sbase + OFF_STAGE + i * 16384, &tm_wq, h * DH + r * 64, i * 128, bar_stage, pol_first);
    }
    const uint32_t kb = sbase + OFF_K + w * (KSM_TILES * 16 * 256);
    {
        const bf16* kq = P.kc + kv_off + KREG_TILES * 16 * DH;
#pragma unroll 1
        for (int it = 0; it < KSM_TILES * 8; it++) {
            const int idx = it * 32 + lane;
            const int row = idx >> 4, ch = idx & 15;
            cp_async16_hint(kb + row * 256 + ((ch ^ (row & 7)) << 4), kq + row * DH + ch * 8, pol_first);
        }
    }
    cp_async_commit();
    if (b < MLP_CTAS) {
#pragma unroll 1
        for (int idx = tid; idx < 2 * D_MODEL; idx += NT) {
            const int row = idx >> 1, hf = idx & 1;
            cp_async16_hint(sbase + OFF_W1 + row * 32 + hf * 16, P.w1 + (size_t)row * FF + b * MLP_UNITS + hf * 8, pol_first);
            const int r2 = idx / 80, ch = idx - r2 * 80;
            cp_async16_hint(sbase + OFF_W2 + r2 * 1280 + ((ch ^ (r2 & 7)) << 4), P.w2 + (size_t)(b * MLP_UNITS) * D_MODEL + idx * 8, pol_first);
        }
    }
    cp_async_commit();
    if (b == 1) for (int e = tid; e < 3 * NREP * D_MODEL; e += NT) (&g_acc[1][0][0])[e] = 0.f;
    uint32_t kreg[KREG_TILES][2][4][4];
    __syncthreads();
    asm volatile("barrier.cluster.arrive.relaxed.aligned;" ::: "memory");
    const unsigned epoch = s_flag[0];
    const unsigned base = epoch << 9;

#pragma unroll 1
    for (int s = 0; s < 4; s++) {
        {
            float v[4] = {0.f, 0.f, 0.f, 0.f};
            if (tid < D_MODEL / 4) {
                const uint2 xr = *reinterpret_cast<const uint2*>(xs + tid * 4);
                v[0] = bflo(xr.x); v[1] = bfhi(xr.x); v[2] = bflo(xr.y); v[3] = bfhi(xr.y);
                if (s != 0) {
                    float4 a = __ldcg(reinterpret_cast<const float4*>(&g_acc[s - 1][0][0]) + tid);
#pragma unroll
                    for (int i = 1; i < NREP; i++) {
                        const float4 a2 = __ldcg(reinterpret_cast<const float4*>(&g_acc[s - 1][i][0]) + tid);
                        a.x += a2.x; a.y += a2.y; a.z += a2.z; a.w += a2.w;
                    }
                    a.x = bf16r(a.x); a.y = bf16r(a.y); a.z = bf16r(a.z); a.w = bf16r(a.w);
                    if (s == 2) {
                        const uint2 br = *reinterpret_cast<const uint2*>(b2s + tid * 4);
                        a.x = bf16r(a.x + bflo(br.x)); a.y = bf16r(a.y + bfhi(br.x));
                        a.z = bf16r(a.z + bflo(br.y)); a.w = bf16r(a.w + bfhi(br.y));
                    }
                    v[0] = bf16r(v[0] + a.x); v[1] = bf16r(v[1] + a.y); v[2] = bf16r(v[2] + a.z); v[3] = bf16r(v[3] + a.w);
                    *reinterpret_cast<uint2*>(xs + tid * 4) = make_uint2(pack_bf16(v[0], v[1]), pack_bf16(v[2], v[3]));
                }
            }
            if (s == 2 && b == 0) {
                for (int e = tid; e < NREP * D_MODEL; e += NT) (&g_acc[0][0][0])[e] = 0.f;
            }
#pragma unroll 1
            for (int rep = 0; rep <= (s & 1); rep++) {
                float mean = 0.25f * ((v[0] + v[1]) + (v[2] + v[3]));
                float m2 = (v[0] - mean) * (v[0] - mean) + (v[1] - mean) * (v[1] - mean) +
                           (v[2] - mean) * (v[2] - mean) + (v[3] - mean) * (v[3] - mean);
                float hn = 2.f;
#pragma unroll
                for (int o = 1; o < 32; o <<= 1) {
                    const float mo = __shfl_xor_sync(0xffffffffu, mean, o);
                    const float qo = __shfl_xor_sync(0xffffffffu, m2, o);
                    const float d = mo - mean;
                    m2 = m2 + qo + d * d * hn;
                    mean = 0.5f * (mean + mo);
                    hn *= 2.f;
                }
                float* rd = red + rep * 12;
                if (lane == 0 && w < 5) { rd[2 * w] = mean; rd[2 * w + 1] = m2; }
                __syncthreads();
                float gm = 0.f, gq = 0.f;
#pragma unroll
                for (int i = 0; i < 5; i++) { gm += rd[2 * i]; gq += rd[2 * i + 1]; }
                gm *= 0.2f;
#pragma unroll
                for (int i = 0; i < 5; i++) { const float d = rd[2 * i] - gm; gq += 128.f * d * d; }
                const float mb = bf16r(gm);
                const float den = bf16r(sqrtf(bf16r(bf16r(gq * (1.0f / D_MODEL)) + 1e-5f)));
#pragma unroll
                for (int i = 0; i < 4; i++) v[i] = bf16r(__fdividef(bf16r(v[i] - mb), den));
            }
            if (tid < D_MODEL / 4)
                *reinterpret_cast<uint2*>(xn + tid * 4) = make_uint2(pack_bf16(v[0], v[1]), pack_bf16(v[2], v[3]));
        }
        if (s == 1) cp_async_wait_all();
        __syncthreads();
        TS(1 + s * 6);
        TS2(0);
        float* acc = &g_acc[s][b & (NREP - 1)][0];

        if (!(s & 1)) {
            const int pass = s >> 1;
            mbar_wait(bar_stage, 0);
            {
                float cq[4][4];
#pragma unroll
                for (int i = 0; i < 4; i++) { cq[i][0] = cq[i][1] = cq[i][2] = cq[i][3] = 0.f; }
#pragma unroll
                for (int k5 = 0; k5 < 5; k5++) {
                    const int ks = w * 5 + k5;
                    const uint32_t b0 = *reinterpret_cast<const uint32_t*>(xn + ks * 16 + 2 * t);
                    const uint32_t b1 = *reinterpret_cast<const uint32_t*>(xn + ks * 16 + 2 * t + 8);
                    const int krow = ks * 16 + (lane & 7) + ((lane >> 4) & 1) * 8;
#pragma unroll
                    for (int mt = 0; mt < 4; mt++) {
                        uint32_t a[4];
                        ldmatrix4t(a, sbase + OFF_STAGE + krow * 128 + (((2 * mt + ((lane >> 3) & 1)) ^ (lane & 7)) << 4));
                        mma16816(cq[mt], a[0], a[1], a[2], a[3], b0, b1);
                    }
                }
                if (t == 0) {
#pragma unroll
                    for (int mt = 0; mt < 4; mt++) { oscr[w * 64 + mt * 16 + g] = cq[mt][0]; oscr[w * 64 + mt * 16 + 8 + g] = cq[mt][2]; }
                }
            }
            TS2(1);
            __syncthreads();
            TS2(2);
            if (s == 0) asm volatile("barrier.cluster.wait.aligned;" ::: "memory");
            if (tid < 32) {
                float s0 = 0.f, s1 = 0.f;
#pragma unroll
                for (int i = 0; i < 8; i++) { const float2 v2 = *reinterpret_cast<const float2*>(oscr + i * 64 + 2 * tid); s0 += v2.x; s1 += v2.y; }
                const uint32_t qp = pack_bf16(s0, s1);
                *reinterpret_cast<uint32_t*>(qs + r * 64 + 2 * tid) = qp;
                st_async_b32(mapa(sbase + OFF_Q + (r * 64 + 2 * tid) * 2, r ^ 1), qp, mapa(sbase + OFF_XBAR, r ^ 1));
                if (tid == 0) { mbar_expect_tx(sbase + OFF_XBAR, 128); mbar_expect_tx(sbase + OFF_XBAR + 8, 256); }
            }
            const uint32_t vland = sbase + OFF_STAGE + w * (VL * 4096);
#pragma unroll 1
            for (int it = 0; it < VL * 8; it++) {
                const int idx = it * 32 + lane;
                const int row = idx >> 4, ch = idx & 15;
                asm volatile("cp.async.cg.shared.global [%0], [%1], 16;" :: "r"(vland + row * 256 + ((ch ^ (row & 7)) << 4)),
                             "l"(P.vc + kv_off + row * DH + ch * 8) : "memory");
            }
            cp_async_commit();
            if (s == 0) {
                const bf16* kp = P.kc + kv_off + (g * DH + t * 8);
#pragma unroll
                for (int i = 0; i < KREG_TILES; i++)
#pragma unroll
                    for (int hh = 0; hh < 2; hh++)
#pragma unroll
                        for (int j = 0; j < 4; j++)
                            ldg128_hint(kreg[i][hh][j], kp + (i * 16 + hh * 8) * DH + j * 32, pol_first);
                if (VPRE > 0 && lane == 0) bulk_prefetch_l2(P.vc + kv_off, VPRE);
            }
            TS2(3);
            __syncthreads();
            mbar_wait(sbase + OFF_XBAR, pass);
            TS2(4);

            float sc[8][2];
            {
                float cacc[KREG_TILES][4];
#pragma unroll
                for (int i = 0; i < KREG_TILES; i++) { cacc[i][0] = cacc[i][1] = cacc[i][2] = cacc[i][3] = 0.f; }
#pragma unroll
                for (int j = 0; j < 4; j++) {
                    const uint4 qv = *reinterpret_cast<const uint4*>(qs + j * 32 + t * 8);
#pragma unroll
                    for (int i = 0; i < KREG_TILES; i++) {
                        mma16816(cacc[i], kreg[i][0][j][0], kreg[i][1][j][0], kreg[i][0][j][1], kreg[i][1][j][1], qv.x, qv.y);
                        mma16816(cacc[i], kreg[i][0][j][2], kreg[i][1][j][2], kreg[i][0][j][3], kreg[i][1][j][3], qv.z, qv.w);
                    }
                }
#pragma unroll
                for (int i = 0; i < KREG_TILES; i++) { sc[i][0] = cacc[i][0]; sc[i][1] = cacc[i][2]; }
            }
            {
                TS2(5);
                if (s == 0) {
                    if (lane == 0) bulk_prefetch_l2(P.vc + kv_off + VL * 16 * DH, (8 - VL) * 4096);
                    cp_async_wait_group<2>();
                    __syncwarp();
                }
                float cacc[KSM_TILES][4];
#pragma unroll
                for (int tt = 0; tt < KSM_TILES; tt++) { cacc[tt][0] = cacc[tt][1] = cacc[tt][2] = cacc[tt][3] = 0.f; }
                const int row0 = (lane & 7) + ((lane >> 3) & 1) * 8;
#pragma unroll 4
                for (int ks = 0; ks < 8; ks++) {
                    const uint32_t b0 = *reinterpret_cast<const uint32_t*>(qs + ks * 16 + 2 * t);
                    const uint32_t b1 = *reinterpret_cast<const uint32_t*>(qs + ks * 16 + 2 * t + 8);
                    const int ch = 2 * ks + (lane >> 4);
                    const uint32_t ad = kb + row0 * 256 + ((ch ^ (lane & 7)) << 4);
#pragma unroll
                    for (int tt = 0; tt < KSM_TILES; tt++) {
                        uint32_t a[4];
                        ldmatrix4(a, ad + tt * 4096);
                        mma16816(cacc[tt], a[0], a[1], a[2], a[3], b0, b1);
                    }
                }
#pragma unroll
                for (int tt = 0; tt < KSM_TILES; tt++) { sc[KREG_TILES + tt][0] = cacc[tt][0]; sc[KREG_TILES + tt][1] = cacc[tt][2]; }
            }
            TS2(6);
            bf16* pw = reinterpret_cast<bf16*>(sm + OFF_P + w * 256);
            {
                float s4[4];
#pragma unroll
                for (int q2 = 0; q2 < 4; q2++) {
                    const int i = q2 >> 1, k2 = q2 & 1;
                    const float v01 = (t & 1) ? sc[2 + i][k2] : sc[i][k2];
                    const float v23 = (t & 1) ? sc[6 + i][k2] : sc[4 + i][k2];
                    s4[q2] = (t & 2) ? v23 : v01;
                }
                float mx = -INFINITY;
#pragma unroll
                for (int q2 = 0; q2 < 4; q2++) {
                    s4[q2] = bf16r(bf16r(s4[q2]) * 0.08838834764831845f);
                    mx = fmaxf(mx, s4[q2]);
                }
#pragma unroll
                for (int o = 1; o < 32; o <<= 1) mx = fmaxf(mx, __shfl_xor_sync(0xffffffffu, mx, o));
                float l = 0.f;
#pragma unroll
                for (int q2 = 0; q2 < 4; q2++) {
                    const bf16 pb = __float2bfloat16_rn(ex2((s4[q2] - mx) * LOG2E));
                    l += __bfloat162float(pb);
                    pw[(2 * t + (q2 >> 1)) * 16 + (q2 & 1) * 8 + g] = pb;
                }
                l = warp_sum(l);
                if (lane == 0) { stat[2 * w] = mx; stat[2 * w + 1] = l; }
            }
            TS2(7);
            __syncthreads();
            TS(2 + s * 6);
            float m_cta = stat[0];
#pragma unroll
            for (int i = 1; i < 8; i++) m_cta = fmaxf(m_cta, stat[2 * i]);
            const float wfac = ex2((stat[2 * w] - m_cta) * LOG2E);
            if (tid == 0) {
                float l_cta = 0.f;
#pragma unroll
                for (int i = 0; i < 8; i++) l_cta += stat[2 * i + 1] * ex2((stat[2 * i] - m_cta) * LOG2E);
                asm volatile("st.relaxed.gpu.global.v4.u32 [%0], {%1,%2,%3,%4};" :: "l"(&g_ml[pass][b]),
                             "r"(__float_as_uint(m_cta)), "r"(__float_as_uint(l_cta)), "r"(epoch * 2 + pass + 1), "r"(0u) : "memory");
            }

            {
                const bf16* vbase = P.vc + kv_off + (4 * t) * DH + g * 8;
                float* ow = oscr + w * 128;
                cp_async_wait_all();
                __syncwarp();
#pragma unroll 1
                for (int mt = 0; mt < 8; mt++) {
                    float cl[4] = {0.f, 0.f, 0.f, 0.f};
#pragma unroll
                    for (int kt = 0; kt < VL; kt++) {
                        const uint32_t b0 = *reinterpret_cast<const uint32_t*>(pw + kt * 16 + 2 * t);
                        const uint32_t b1 = *reinterpret_cast<const uint32_t*>(pw + kt * 16 + 2 * t + 8);
                        const int row = kt * 16 + (lane & 7) + ((lane >> 4) & 1) * 8;
                        uint32_t a[4];
                        ldmatrix4t(a, vland + row * 256 + (((2 * mt + ((lane >> 3) & 1)) ^ (lane & 7)) << 4));
                        mma16816(cl, a[0], a[1], a[2], a[3], b0, b1);
                    }
                    if (t == 0) { ow[mt * 16 + g] = cl[0] * wfac; ow[mt * 16 + 8 + g] = cl[2] * wfac; }
                }
                __syncthreads();
                if (tid == 224) {
                    mbar_expect_tx(bar_stage, 81920);
#pragma unroll 1
                    for (int i = 0; i < 10; i++) tma_2d_hint(sbase + OFF_STAGE + i * 8192, &tm_wo, i * 64, h * DH + r * 64, bar_stage, pol_first);
                }
                float oacc[4][4];
#pragma unroll
                for (int i = 0; i < 4; i++) { oacc[i][0] = oacc[i][1] = oacc[i][2] = oacc[i][3] = 0.f; }
                constexpr int NK = 8 - VL;
                uint32_t vbuf[2][4][4];
#pragma unroll
                for (int i = 0; i < 4; i++) ldg128(vbuf[0][i], vbase + (VL * 16 + i) * DH);
#pragma unroll 1
                for (int hf = 0; hf < 2; hf++) {
#pragma unroll 1
                    for (int k0 = 0; k0 < NK; k0 += 2) {
#pragma unroll
                        for (int u = 0; u < 2; u++) {
                            const int kt = k0 + u;
                            int nk = kt + 1, nh = hf;
                            if (nk == NK) { nk = 0; nh = hf + 1; }
                            if (nh < 2) {
                                const bf16* vp = vbase + (VL + nk) * 16 * DH + nh * 64;
#pragma unroll
                                for (int i = 0; i < 4; i++) ldg128(vbuf[u ^ 1][i], vp + i * DH);
                            }
                            const uint2 pb = *reinterpret_cast<const uint2*>(pw + (VL + kt) * 16 + 4 * t);
#pragma unroll
                            for (int e = 0; e < 4; e++)
                                mma16816(oacc[e], __byte_perm(vbuf[u][0][e], vbuf[u][1][e], 0x5410), __byte_perm(vbuf[u][0][e], vbuf[u][1][e], 0x7632),
                                         __byte_perm(vbuf[u][2][e], vbuf[u][3][e], 0x5410), __byte_perm(vbuf[u][2][e], vbuf[u][3][e], 0x7632), pb.x, pb.y);
                        }
                    }
                    if (t == 0) {
                        float* o2 = ow + hf * 64 + g * 8;
                        float4 u0 = *reinterpret_cast<float4*>(o2), u1 = *reinterpret_cast<float4*>(o2 + 4);
                        u0.x += oacc[0][0] * wfac; u0.y += oacc[0][2] * wfac; u0.z += oacc[1][0] * wfac; u0.w += oacc[1][2] * wfac;
                        u1.x += oacc[2][0] * wfac; u1.y += oacc[2][2] * wfac; u1.z += oacc[3][0] * wfac; u1.w += oacc[3][2] * wfac;
                        *reinterpret_cast<float4*>(o2) = u0;
                        *reinterpret_cast<float4*>(o2 + 4) = u1;
                    }
#pragma unroll
                    for (int i = 0; i < 4; i++) { oacc[i][0] = oacc[i][1] = oacc[i][2] = oacc[i][3] = 0.f; }
                }
            }
            __syncthreads();
            TS(3 + s * 6);
            TS2(10);
            if (tid < 128) {
                uint4 rec[4];
                {
                    unsigned it = 0;
                    const unsigned tag = epoch * 2 + pass + 1;
                    while (true) {
#pragma unroll
                        for (int i = 0; i < 4; i++)
                            asm volatile("ld.relaxed.gpu.global.v4.u32 {%0,%1,%2,%3}, [%4];"
                                         : "=r"(rec[i].x), "=r"(rec[i].y), "=r"(rec[i].z), "=r"(rec[i].w)
                                         : "l"(&g_ml[pass][(b & ~3) + i]) : "memory");
                        if (rec[0].z == tag && rec[1].z == tag && rec[2].z == tag && rec[3].z == tag) break;
                        if (++it > SPIN_LIMIT) __trap();
                    }
                }
                const float M = fmaxf(fmaxf(__uint_as_float(rec[0].x), __uint_as_float(rec[1].x)),
                                      fmaxf(__uint_as_float(rec[2].x), __uint_as_float(rec[3].x)));
                float L = 0.f;
#pragma unroll
                for (int i = 0; i < 4; i++) L += __uint_as_float(rec[i].y) * ex2((__uint_as_float(rec[i].x) - M) * LOG2E);
                const float scale = __fdividef(ex2((m_cta - M) * LOG2E), L);
                float sum = 0.f;
#pragma unroll
                for (int i = 0; i < 8; i++) sum += oscr[i * 128 + tid];
                if ((tid >> 6) == r) oex[r * 64 + (tid & 63)] = sum * scale;
                else st_async_b32(mapa(sbase + OFF_OEX + (r * 64 + (tid & 63)) * 4, r ^ 1), __float_as_uint(sum * scale), mapa(sbase + OFF_XBAR + 8, r ^ 1));
            }
            TS2(8);
            __syncthreads();
            TS2(9);
            if (tid < 64) {
                mbar_wait(sbase + OFF_XBAR + 8, pass);
                const float o = oex[tid] + oex[64 + tid];
                const bf16 hi = __float2bfloat16_rn(o);
                hs[32 + tid] = hi;
                hs[96 + tid] = __float2bfloat16_rn(o - __bfloat162float(hi));
            }
            mbar_wait(bar_stage, 1);
            __syncthreads();
            TS(4 + s * 6);
            {
                float co[5][4];
#pragma unroll
                for (int i = 0; i < 5; i++) { co[i][0] = co[i][1] = co[i][2] = co[i][3] = 0.f; }
#pragma unroll 1
                for (int ks = 0; ks < 4; ks++) {
                    uint32_t b0 = 0, b1 = 0;
                    if (g < 2) {
                        b0 = *reinterpret_cast<const uint32_t*>(hs + 32 + g * 64 + ks * 16 + 2 * t);
                        b1 = *reinterpret_cast<const uint32_t*>(hs + 32 + g * 64 + ks * 16 + 2 * t + 8);
                    }
                    const int krow = ks * 16 + (lane & 7) + ((lane >> 4) & 1) * 8;
#pragma unroll
                    for (int i = 0; i < 5; i++) {
                        const int ch = 2 * (w * 5 + i) + ((lane >> 3) & 1);
                        uint32_t a[4];
                        ldmatrix4t(a, sbase + OFF_STAGE + (ch >> 3) * 8192 + krow * 128 + (((ch ^ lane) & 7) << 4));
                        mma16816(co[i], a[0], a[1], a[2], a[3], b0, b1);
                    }
                }
                if (t == 0) {
#pragma unroll
                    for (int i = 0; i < 5; i++) {
                        red_add(acc + (w * 5 + i) * 16 + g, co[i][0] + co[i][1]);
                        red_add(acc + (w * 5 + i) * 16 + 8 + g, co[i][2] + co[i][3]);
                    }
                }
            }
            if (s == 0) {
                __syncthreads();
                if (tid == 224) {
                    mbar_expect_tx(bar_stage, 81920);
#pragma unroll 1
                    for (int i = 0; i < 5; i++) tma_2d_hint(sbase + OFF_STAGE + i * 16384, &tm_wq, h * DH + r * 64, i * 128, bar_stage, pol_first);
                }
            }
        } else if (b < MLP_CTAS) {
            {
                float ch4[4] = {0.f, 0.f, 0.f, 0.f};
#pragma unroll
                for (int k5 = 0; k5 < 5; k5++) {
                    const int ks = w * 5 + k5;
                    const uint32_t b0 = *reinterpret_cast<const uint32_t*>(xn + ks * 16 + 2 * t);
                    const uint32_t b1 = *reinterpret_cast<const uint32_t*>(xn + ks * 16 + 2 * t + 8);
                    const int krow = ks * 16 + (lane & 7) + ((lane >> 4) & 1) * 8;
                    uint32_t a[4];
                    ldmatrix4t(a, sbase + OFF_W1 + krow * 32 + ((lane >> 3) & 1) * 16);
                    mma16816(ch4, a[0], a[1], a[2], a[3], b0, b1);
                }
                if (t == 0) { oscr[w * 16 + g] = ch4[0]; oscr[w * 16 + 8 + g] = ch4[2]; }
            }
            __syncthreads();
            if (tid < 16) {
                float sum = 0.f;
#pragma unroll
                for (int i = 0; i < 8; i++) sum += oscr[i * 16 + tid];
                const float u = bf16r(bf16r(sum) + __bfloat162float(hs[16 + tid]));
                const float inner = 0.7978845608028654f * (u + 0.044715f * u * u * u);
                hs[tid] = __float2bfloat16_rn(0.5f * u * (1.0f + tanhf(inner)));
            }
            __syncthreads();
            {
                const uint32_t b0 = *reinterpret_cast<const uint32_t*>(hs + 2 * t);
                const uint32_t b1 = *reinterpret_cast<const uint32_t*>(hs + 2 * t + 8);
                const int krow = (lane & 7) + ((lane >> 4) & 1) * 8;
#pragma unroll
                for (int i = 0; i < 5; i++) {
                    const int ch = 2 * (w * 5 + i) + ((lane >> 3) & 1);
                    uint32_t a[4];
                    float co[4] = {0.f, 0.f, 0.f, 0.f};
                    ldmatrix4t(a, sbase + OFF_W2 + krow * 1280 + ((ch ^ (lane & 7)) << 4));
                    mma16816(co, a[0], a[1], a[2], a[3], b0, b1);
                    if (t == 0) {
                        red_add(acc + (w * 5 + i) * 16 + g, co[0]);
                        red_add(acc + (w * 5 + i) * 16 + 8 + g, co[2]);
                    }
                }
            }
        }
        TS(5 + s * 6);
        TS2(11);
        if (s < 3) grid_barrier(base + NCTA * (s + 1));
        TS(6 + s * 6);
    }
    __syncthreads();
    if (tid == 0) {
        __threadfence();
        const unsigned old = atomicAdd(&g_ctr, 1u);
        s_flag[1] = (old == base + 4 * NCTA - 1) ? 1u : 0u;
        __threadfence();
    }
    __syncthreads();
    if (s_flag[1]) {
        for (int e = tid; e < D_MODEL; e += NT) {
            float a = 0.f;
#pragma unroll
            for (int i = 0; i < NREP; i++) a += __ldcg(&g_acc[3][i][e]);
            const float o = bf16r(bf16r(a) + __bfloat162float(b2s[e]));
            P.out[e] = __float2bfloat16_rn(__bfloat162float(xs[e]) + o);
        }
    }
    TS(25);
}

}

extern "C" void kernel_launch(void* const* d_in, const int* in_sizes, int n_in,
                              void* d_out, int out_size) {
    Params P;
    P.x = (const bf16*)d_in[0];
    P.kc = (const bf16*)d_in[1];
    P.vc = (const bf16*)d_in[2];
    P.wq = (const bf16*)d_in[3];
    P.wo = (const bf16*)d_in[4];
    P.w1 = (const bf16*)d_in[6];
    P.b1 = (const bf16*)d_in[7];
    P.w2 = (const bf16*)d_in[8];
    P.b2 = (const bf16*)d_in[9];
    P.out = (bf16*)d_out;

    cudaFuncSetAttribute(fused_kernel, cudaFuncAttributeMaxDynamicSharedMemorySize, SMEM_BYTES);

    typedef CUresult (*EncodeFn)(CUtensorMap*, CUtensorMapDataType, cuuint32_t, void*, const cuuint64_t*, const cuuint64_t*,
                                 const cuuint32_t*, const cuuint32_t*, CUtensorMapInterleave, CUtensorMapSwizzle,
                                 CUtensorMapL2promotion, CUtensorMapFloatOOBfill);
    void* fn = nullptr;
    cudaDriverEntryPointQueryResult qres;
    cudaGetDriverEntryPoint("cuTensorMapEncodeTiled", &fn, cudaEnableDefault, &qres);
    EncodeFn encode = (EncodeFn)fn;
    CUtensorMap tm_wq, tm_wo;
    {
        cuuint64_t dims[2] = {(cuuint64_t)(NHEAD * DH), (cuuint64_t)D_MODEL};
        cuuint64_t strides[1] = {(cuuint64_t)(NHEAD * DH * 2)};
        cuuint32_t box[2] = {64, 128};
        cuuint32_t es[2] = {1, 1};
        encode(&tm_wq, CU_TENSOR_MAP_DATA_TYPE_BFLOAT16, 2, (void*)P.wq, dims, strides, box, es, CU_TENSOR_MAP_INTERLEAVE_NONE,
               CU_TENSOR_MAP_SWIZZLE_128B, CU_TENSOR_MAP_L2_PROMOTION_NONE, CU_TENSOR_MAP_FLOAT_OOB_FILL_NONE);
    }
    {
        cuuint64_t dims[2] = {(cuuint64_t)D_MODEL, (cuuint64_t)(NHEAD * DH)};
        cuuint64_t strides[1] = {(cuuint64_t)(D_MODEL * 2)};
        cuuint32_t box[2] = {64, 64};
        cuuint32_t es[2] = {1, 1};
        encode(&tm_wo, CU_TENSOR_MAP_DATA_TYPE_BFLOAT16, 2, (void*)P.wo, dims, strides, box, es, CU_TENSOR_MAP_INTERLEAVE_NONE,
               CU_TENSOR_MAP_SWIZZLE_128B, CU_TENSOR_MAP_L2_PROMOTION_NONE, CU_TENSOR_MAP_FLOAT_OOB_FILL_NONE);
    }

    cudaLaunchConfig_t cfg = {};
    cfg.gridDim = dim3(NCTA);
    cfg.blockDim = dim3(NT);
    cfg.dynamicSmemBytes = SMEM_BYTES;
    cfg.stream = cudaStreamPerThread;
    cudaLaunchAttribute at[2];
    at[0].id = cudaLaunchAttributeClusterDimension;
    at[0].val.clusterDim.x = 2; at[0].val.clusterDim.y = 1; at[0].val.clusterDim.z = 1;
    at[1].id = cudaLaunchAttributeCooperative;
    at[1].val.cooperative = 1;
    cfg.attrs = at;
    cfg.numAttrs = 2;
    cudaLaunchKernelEx(&cfg, fused_kernel, P, tm_wq, tm_wo);
}
```

```cpp
#include <cuda_runtime.h>
#include <cuda.h>
#include <cuda_bf16.h>
#include <stdint.h>

typedef __nv_bfloat16 bf16;

namespace {

constexpr int D_MODEL = 640;
constexpr int NHEAD = 32;
constexpr int SEQ = 4096;
constexpr int DH = 128;
constexpr int FF = 1728;
constexpr int NCTA = 128;
constexpr int NT = 256;
constexpr int KREG_TILES = 5;
constexpr int KSM_TILES = 3;
constexpr int MLP_UNITS = 16;
constexpr int MLP_CTAS = FF / MLP_UNITS;

constexpr int OFF_STAGE = 0;
constexpr int OFF_W2 = 81920;
constexpr int OFF_W1 = OFF_W2 + 20480;
constexpr int OFF_K = OFF_W1 + 20480;
constexpr int OFF_XS = OFF_K + 98304;
constexpr int OFF_XN = OFF_XS + 1280;
constexpr int OFF_O = OFF_XN + 1280;
constexpr int OFF_P = OFF_O + 4096;
constexpr int OFF_Q = OFF_P + 2048;
constexpr int OFF_OEX = OFF_Q + 256;
constexpr int OFF_STAT = OFF_OEX + 512;
constexpr int OFF_RED = OFF_STAT + 80;
constexpr int OFF_HS = OFF_RED + 96;
constexpr int OFF_B2 = OFF_HS + 320;
constexpr int OFF_XBAR = OFF_B2 + 1280;
constexpr int SMEM_BYTES = OFF_XBAR + 16;

static_assert(SMEM_BYTES <= 232448, "smem");
constexpr int NREP = 4;
constexpr int VL = 2;
#define VPRE 0
#ifndef NVB
#define NVB 2
#endif
constexpr unsigned SPIN_LIMIT = 1u << 24;

__device__ unsigned int g_ctr;
__device__ float g_acc[4][NREP][D_MODEL];
__device__ uint4 g_ml[2][NCTA];

#define TS(i) do {} while (0)
#define TS2(i) do {} while (0)

struct Params {
    const bf16* x; const bf16* kc; const bf16* vc; const bf16* wq; const bf16* wo;
    const bf16* w1; const bf16* b1; const bf16* w2; const bf16* b2; bf16* out;
};

__device__ __forceinline__ float bf16r(float x) { return __bfloat162float(__float2bfloat16_rn(x)); }
__device__ __forceinline__ float bflo(uint32_t u) { return __uint_as_float(u << 16); }
__device__ __forceinline__ float bfhi(uint32_t u) { return __uint_as_float(u & 0xffff0000u); }

__device__ __forceinline__ uint32_t smem_u32(const void* p) { return (uint32_t)__cvta_generic_to_shared(p); }

__device__ __forceinline__ void mbar_init(uint32_t bar, uint32_t cnt) {
    asm volatile("mbarrier.init.shared::cta.b64 [%0], %1;" :: "r"(bar), "r"(cnt) : "memory");
}
__device__ __forceinline__ void mbar_expect_tx(uint32_t bar, uint32_t bytes) {
    asm volatile("mbarrier.arrive.expect_tx.shared::cta.b64 _, [%0], %1;" :: "r"(bar), "r"(bytes) : "memory");
}
__device__ __forceinline__ void mbar_wait(uint32_t bar, uint32_t parity) {
    unsigned it = 0;
    while (true) {
        uint32_t ok;
        asm volatile("{\n\t.reg .pred p;\n\tmbarrier.try_wait.parity.shared::cta.b64 p, [%1], %2;\n\tselp.u32 %0, 1, 0, p;\n\t}"
                     : "=r"(ok) : "r"(bar), "r"(parity) : "memory");
        if (ok) break;
        if (++it > SPIN_LIMIT) __trap();
    }
}
__device__ __forceinline__ void bulk_g2s(uint32_t dst, const void* src, uint32_t bytes, uint32_t bar) {
    asm volatile("cp.async.bulk.shared::cluster.global.mbarrier::complete_tx::bytes [%0], [%1], %2, [%3];"
                 :: "r"(dst), "l"(src), "r"(bytes), "r"(bar) : "memory");
}
__device__ __forceinline__ void bulk_g2s_hint(uint32_t dst, const void* src, uint32_t bytes, uint32_t bar, uint64_t pol) {
    asm volatile("cp.async.bulk.shared::cluster.global.mbarrier::complete_tx::bytes.L2::cache_hint [%0], [%1], %2, [%3], %4;"
                 :: "r"(dst), "l"(src), "r"(bytes), "r"(bar), "l"(pol) : "memory");
}
__device__ __forceinline__ void tma_2d_hint(uint32_t dst, const CUtensorMap* tm, int c0, int c1, uint32_t bar, uint64_t pol) {
    asm volatile("cp.async.bulk.tensor.2d.shared::cluster.global.mbarrier::complete_tx::bytes.L2::cache_hint [%0], [%1, {%3, %4}], [%2], %5;"
                 :: "r"(dst), "l"(tm), "r"(bar), "r"(c0), "r"(c1), "l"(pol) : "memory");
}
__device__ __forceinline__ void bulk_prefetch_l2(const void* src, uint32_t bytes) {
    asm volatile("cp.async.bulk.prefetch.L2.global [%0], %1;" :: "l"(src), "r"(bytes) : "memory");
}
__device__ __forceinline__ void bulk_prefetch_l2_hint(const void* src, uint32_t bytes, uint64_t pol) {
    asm volatile("cp.async.bulk.prefetch.L2.global.L2::cache_hint [%0], %1, %2;" :: "l"(src), "r"(bytes), "l"(pol) : "memory");
}
__device__ __forceinline__ float ex2(float x) { float y; asm("ex2.approx.ftz.f32 %0, %1;" : "=f"(y) : "f"(x)); return y; }
__device__ __forceinline__ void cp_async16_hint(uint32_t dst, const void* src, uint64_t pol) {
    asm volatile("cp.async.cg.shared.global.L2::cache_hint [%0], [%1], 16, %2;" :: "r"(dst), "l"(src), "l"(pol) : "memory");
}
__device__ __forceinline__ void cp_async_wait_all() { asm volatile("cp.async.wait_all;" ::: "memory"); }
__device__ __forceinline__ void cp_async_commit() { asm volatile("cp.async.commit_group;" ::: "memory"); }
template <int N> __device__ __forceinline__ void cp_async_wait_group() { asm volatile("cp.async.wait_group %0;" :: "n"(N) : "memory"); }

__device__ __forceinline__ void ldg128_hint(uint32_t (&r)[4], const void* p, uint64_t pol) {
    asm volatile("ld.global.nc.L1::no_allocate.L2::cache_hint.v4.u32 {%0,%1,%2,%3}, [%4], %5;"
                 : "=r"(r[0]), "=r"(r[1]), "=r"(r[2]), "=r"(r[3]) : "l"(p), "l"(pol));
}
__device__ __forceinline__ void ldg128(uint32_t (&r)[4], const void* p) {
    asm volatile("ld.global.nc.v4.u32 {%0,%1,%2,%3}, [%4];"
                 : "=r"(r[0]), "=r"(r[1]), "=r"(r[2]), "=r"(r[3]) : "l"(p));
}
__device__ __forceinline__ void mma16816(float (&c)[4], uint32_t a0, uint32_t a1, uint32_t a2, uint32_t a3,
                                         uint32_t b0, uint32_t b1) {
    asm volatile("mma.sync.aligned.m16n8k16.row.col.f32.bf16.bf16.f32 {%0,%1,%2,%3}, {%4,%5,%6,%7}, {%8,%9}, {%0,%1,%2,%3};"
                 : "+f"(c[0]), "+f"(c[1]), "+f"(c[2]), "+f"(c[3])
                 : "r"(a0), "r"(a1), "r"(a2), "r"(a3), "r"(b0), "r"(b1));
}
__device__ __forceinline__ void ldmatrix4(uint32_t (&r)[4], uint32_t addr) {
    asm volatile("ldmatrix.sync.aligned.m8n8.x4.shared.b16 {%0,%1,%2,%3}, [%4];"
                 : "=r"(r[0]), "=r"(r[1]), "=r"(r[2]), "=r"(r[3]) : "r"(addr) : "memory");
}
__device__ __forceinline__ void red_add_v4(float* p, float a, float b, float c, float d) {
    asm volatile("red.global.add.v4.f32 [%0], {%1,%2,%3,%4};" :: "l"(p), "f"(a), "f"(b), "f"(c), "f"(d) : "memory");
}
__device__ __forceinline__ unsigned ld_acquire(const unsigned* p) {
    unsigned v; asm volatile("ld.acquire.gpu.global.u32 %0, [%1];" : "=r"(v) : "l"(p) : "memory"); return v;
}
__device__ __forceinline__ void st_release(unsigned* p, unsigned v) {
    asm volatile("st.release.gpu.global.u32 [%0], %1;" :: "l"(p), "r"(v) : "memory");
}
__device__ __forceinline__ void cluster_sync_all() {
    asm volatile("barrier.cluster.arrive.release.aligned;\n\tbarrier.cluster.wait.acquire.aligned;" ::: "memory");
}
__device__ __forceinline__ uint32_t mapa(uint32_t addr, uint32_t rank) {
    uint32_t r; asm volatile("mapa.shared::cluster.u32 %0, %1, %2;" : "=r"(r) : "r"(addr), "r"(rank)); return r;
}
__device__ __forceinline__ void st_async_b32(uint32_t addr, uint32_t v, uint32_t bar) {
    asm volatile("st.async.weak.shared::cluster.mbarrier::complete_tx::bytes.b32 [%0], %1, [%2];" :: "r"(addr), "r"(v), "r"(bar) : "memory");
}
__device__ __forceinline__ void st_cluster_f32(uint32_t addr, float v) {
    asm volatile("st.shared::cluster.f32 [%0], %1;" :: "r"(addr), "f"(v) : "memory");
}
__device__ __forceinline__ void st_cluster_u16(uint32_t addr, uint16_t v) {
    asm volatile("st.shared::cluster.u16 [%0], %1;" :: "r"(addr), "h"(v) : "memory");
}
__device__ __forceinline__ float warp_sum(float v) {
#pragma unroll
    for (int o = 16; o > 0; o >>= 1) v += __shfl_xor_sync(0xffffffffu, v, o);
    return v;
}

__device__ __forceinline__ void grid_barrier(unsigned target) {
    __syncthreads();
    if (threadIdx.x == 0) {
        __threadfence();
        atomicAdd(&g_ctr, 1u);
        unsigned it = 0;
        while ((int)(ld_acquire(&g_ctr) - target) < 0) { if (++it > SPIN_LIMIT) __trap(); }
    }
    __syncthreads();
}

constexpr float LOG2E = 1.4426950408889634f;

__device__ __forceinline__ void ldmatrix4t(uint32_t (&r)[4], uint32_t addr) {
    asm volatile("ldmatrix.sync.aligned.m8n8.x4.trans.shared.b16 {%0,%1,%2,%3}, [%4];"
                 : "=r"(r[0]), "=r"(r[1]), "=r"(r[2]), "=r"(r[3]) : "r"(addr) : "memory");
}
__device__ __forceinline__ void red_add(float* p, float a) {
    asm volatile("red.global.add.f32 [%0], %1;" :: "l"(p), "f"(a) : "memory");
}
__device__ __forceinline__ uint32_t pack_bf16(float lo, float hi) {
    uint32_t r; asm("cvt.rn.bf16x2.f32 %0, %1, %2;" : "=r"(r) : "f"(hi), "f"(lo)); return r;
}

__global__ void __launch_bounds__(NT, 1) fused_kernel(const Params P, const __grid_constant__ CUtensorMap tm_wq,
                                                        const __grid_constant__ CUtensorMap tm_wo) {
    extern __shared__ __align__(1024) unsigned char sm[];
    const int tid = threadIdx.x, lane = tid & 31, w = tid >> 5;
    const int g = lane >> 2, t = lane & 3;
    const int b = blockIdx.x, h = b >> 2, c = b & 3, r = b & 1;
    const uint32_t sbase = smem_u32(sm);
    bf16* xs = reinterpret_cast<bf16*>(sm + OFF_XS);
    bf16* xn = reinterpret_cast<bf16*>(sm + OFF_XN);
    bf16* b2s = reinterpret_cast<bf16*>(sm + OFF_B2);
    float* oscr = reinterpret_cast<float*>(sm + OFF_O);
    bf16* qs = reinterpret_cast<bf16*>(sm + OFF_Q);
    float* oex = reinterpret_cast<float*>(sm + OFF_OEX);
    float* stat = reinterpret_cast<float*>(sm + OFF_STAT);
    float* red = reinterpret_cast<float*>(sm + OFF_RED);
    bf16* hs = reinterpret_cast<bf16*>(sm + OFF_HS);
    volatile unsigned* s_flag = reinterpret_cast<volatile unsigned*>(sm + OFF_STAT + 64);
    const uint32_t bar_stage = sbase + OFF_STAT + 72;

    TS(0);
    if (tid < D_MODEL / 8) *reinterpret_cast<uint4*>(xs + tid * 8) = __ldg(reinterpret_cast<const uint4*>(P.x) + tid);
    else if (tid < D_MODEL / 4) *reinterpret_cast<uint4*>(b2s + (tid - 80) * 8) = __ldg(reinterpret_cast<const uint4*>(P.b2) + (tid - 80));
    else if (tid < 162) { if (b < MLP_CTAS) *reinterpret_cast<uint4*>(hs + 16 + (tid - 160) * 8) = __ldg(reinterpret_cast<const uint4*>(P.b1 + b * MLP_UNITS) + (tid - 160)); }
    else if (tid == 192) s_flag[0] = ld_acquire(&g_ctr) >> 9;
    uint64_t pol_first;
    asm volatile("createpolicy.fractional.L2::evict_first.b64 %0, 1.0;" : "=l"(pol_first));
    uint64_t pol_norm;
    asm volatile("createpolicy.fractional.L2::evict_normal.b64 %0, 1.0;" : "=l"(pol_norm));

    const size_t kv_off = (size_t)(h * SEQ + c * 1024 + w * 128) * DH;
    if (tid == 224) {
        mbar_init(bar_stage, 1);
        mbar_init(sbase + OFF_XBAR, 1);
        mbar_init(sbase + OFF_XBAR + 8, 1);
        asm volatile("fence.mbarrier_init.release.cluster;" ::: "memory");
        asm volatile("fence.proxy.async.shared::cta;" ::: "memory");
        mbar_expect_tx(bar_stage, 81920);
#pragma unroll
        for (int i = 0; i < 5; i++) tma_2d_hint(sbase + OFF_STAGE + i * 16384, &tm_wq, h * DH + r * 64, i * 128, bar_stage, pol_first);
    }
    const uint32_t kb = sbase + OFF_K + w * (KSM_TILES * 16 * 256);
    {
        const bf16* kq = P.kc + kv_off + KREG_TILES * 16 * DH;
#pragma unroll 1
        for (int it = 0; it < KSM_TILES * 8; it++) {
            const int idx = it * 32 + lane;
            const int row = idx >> 4, ch = idx & 15;
            cp_async16_hint(kb + row * 256 + ((ch ^ (row & 7)) << 4), kq + row * DH + ch * 8, pol_first);
        }
    }
    cp_async_commit();
    if (b < MLP_CTAS) {
#pragma unroll 1
        for (int idx = tid; idx < 2 * D_MODEL; idx += NT) {
            const int row = idx >> 1, hf = idx & 1;
            cp_async16_hint(sbase + OFF_W1 + row * 32 + hf * 16, P.w1 + (size_t)row * FF + b * MLP_UNITS + hf * 8, pol_first);
            const int r2 = idx / 80, ch = idx - r2 * 80;
            cp_async16_hint(sbase + OFF_W2 + r2 * 1280 + ((ch ^ (r2 & 7)) << 4), P.w2 + (size_t)(b * MLP_UNITS) * D_MODEL + idx * 8, pol_first);
        }
    }
    cp_async_commit();
    if (b == 1) for (int e = tid; e < 3 * NREP * D_MODEL; e += NT) (&g_acc[1][0][0])[e] = 0.f;
    uint32_t kreg[KREG_TILES][2][4][4];
    __syncthreads();
    asm volatile("barrier.cluster.arrive.relaxed.aligned;" ::: "memory");
    const unsigned epoch = s_flag[0];
    const unsigned base = epoch << 9;

#pragma unroll 1
    for (int s = 0; s < 4; s++) {
        {
            float v[4] = {0.f, 0.f, 0.f, 0.f};
            if (tid < D_MODEL / 4) {
                const uint2 xr = *reinterpret_cast<const uint2*>(xs + tid * 4);
                v[0] = bflo(xr.x); v[1] = bfhi(xr.x); v[2] = bflo(xr.y); v[3] = bfhi(xr.y);
                if (s != 0) {
                    float4 a = __ldcg(reinterpret_cast<const float4*>(&g_acc[s - 1][0][0]) + tid);
#pragma unroll
                    for (int i = 1; i < NREP; i++) {
                        const float4 a2 = __ldcg(reinterpret_cast<const float4*>(&g_acc[s - 1][i][0]) + tid);
                        a.x += a2.x; a.y += a2.y; a.z += a2.z; a.w += a2.w;
                    }
                    a.x = bf16r(a.x); a.y = bf16r(a.y); a.z = bf16r(a.z); a.w = bf16r(a.w);
                    if (s == 2) {
                        const uint2 br = *reinterpret_cast<const uint2*>(b2s + tid * 4);
                        a.x = bf16r(a.x + bflo(br.x)); a.y = bf16r(a.y + bfhi(br.x));
                        a.z = bf16r(a.z + bflo(br.y)); a.w = bf16r(a.w + bfhi(br.y));
                    }
                    v[0] = bf16r(v[0] + a.x); v[1] = bf16r(v[1] + a.y); v[2] = bf16r(v[2] + a.z); v[3] = bf16r(v[3] + a.w);
                    *reinterpret_cast<uint2*>(xs + tid * 4) = make_uint2(pack_bf16(v[0], v[1]), pack_bf16(v[2], v[3]));
                }
            }
            if (s == 2 && b == 0) {
                for (int e = tid; e < NREP * D_MODEL; e += NT) (&g_acc[0][0][0])[e] = 0.f;
            }
#pragma unroll 1
            for (int rep = 0; rep <= (s & 1); rep++) {
                float mean = 0.25f * ((v[0] + v[1]) + (v[2] + v[3]));
                float m2 = (v[0] - mean) * (v[0] - mean) + (v[1] - mean) * (v[1] - mean) +
                           (v[2] - mean) * (v[2] - mean) + (v[3] - mean) * (v[3] - mean);
                float hn = 2.f;
#pragma unroll
                for (int o = 1; o < 32; o <<= 1) {
                    const float mo = __shfl_xor_sync(0xffffffffu, mean, o);
                    const float qo = __shfl_xor_sync(0xffffffffu, m2, o);
                    const float d = mo - mean;
                    m2 = m2 + qo + d * d * hn;
                    mean = 0.5f * (mean + mo);
                    hn *= 2.f;
                }
                float* rd = red + rep * 12;
                if (lane == 0 && w < 5) { rd[2 * w] = mean; rd[2 * w + 1] = m2; }
                __syncthreads();
                float gm = 0.f, gq = 0.f;
#pragma unroll
                for (int i = 0; i < 5; i++) { gm += rd[2 * i]; gq += rd[2 * i + 1]; }
                gm *= 0.2f;
#pragma unroll
                for (int i = 0; i < 5; i++) { const float d = rd[2 * i] - gm; gq += 128.f * d * d; }
                const float mb = bf16r(gm);
                const float den = bf16r(sqrtf(bf16r(bf16r(gq * (1.0f / D_MODEL)) + 1e-5f)));
#pragma unroll
                for (int i = 0; i < 4; i++) v[i] = bf16r(__fdividef(bf16r(v[i] - mb), den));
            }
            if (tid < D_MODEL / 4)
                *reinterpret_cast<uint2*>(xn + tid * 4) = make_uint2(pack_bf16(v[0], v[1]), pack_bf16(v[2], v[3]));
        }
        if (s == 1) cp_async_wait_all();
        __syncthreads();
        TS(1 + s * 6);
        TS2(0);
        float* acc = &g_acc[s][b & (NREP - 1)][0];

        if (!(s & 1)) {
            const int pass = s >> 1;
            mbar_wait(bar_stage, 0);
            {
                float cq[4][4];
#pragma unroll
                for (int i = 0; i < 4; i++) { cq[i][0] = cq[i][1] = cq[i][2] = cq[i][3] = 0.f; }
#pragma unroll
                for (int k5 = 0; k5 < 5; k5++) {
                    const int ks = w * 5 + k5;
                    const uint32_t b0 = *reinterpret_cast<const uint32_t*>(xn + ks * 16 + 2 * t);
                    const uint32_t b1 = *reinterpret_cast<const uint32_t*>(xn + ks * 16 + 2 * t + 8);
                    const int krow = ks * 16 + (lane & 7) + ((lane >> 4) & 1) * 8;
#pragma unroll
                    for (int mt = 0; mt < 4; mt++) {
                        uint32_t a[4];
                        ldmatrix4t(a, sbase + OFF_STAGE + krow * 128 + (((2 * mt + ((lane >> 3) & 1)) ^ (lane & 7)) << 4));
                        mma16816(cq[mt], a[0], a[1], a[2], a[3], b0, b1);
                    }
                }
                if (t == 0) {
#pragma unroll
                    for (int mt = 0; mt < 4; mt++) { oscr[w * 64 + mt * 16 + g] = cq[mt][0]; oscr[w * 64 + mt * 16 + 8 + g] = cq[mt][2]; }
                }
            }
            TS2(1);
            __syncthreads();
            TS2(2);
            if (s == 0) asm volatile("barrier.cluster.wait.aligned;" ::: "memory");
            if (tid < 32) {
                float s0 = 0.f, s1 = 0.f;
#pragma unroll
                for (int i = 0; i < 8; i++) { const float2 v2 = *reinterpret_cast<const float2*>(oscr + i * 64 + 2 * tid); s0 += v2.x; s1 += v2.y; }
                const uint32_t qp = pack_bf16(s0, s1);
                *reinterpret_cast<uint32_t*>(qs + r * 64 + 2 * tid) = qp;
                st_async_b32(mapa(sbase + OFF_Q + (r * 64 + 2 * tid) * 2, r ^ 1), qp, mapa(sbase + OFF_XBAR, r ^ 1));
                if (tid == 0) { mbar_expect_tx(sbase + OFF_XBAR, 128); mbar_expect_tx(sbase + OFF_XBAR + 8, 256); }
            }
            const uint32_t vland = sbase + OFF_STAGE + w * (VL * 4096);
#pragma unroll 1
            for (int it = 0; it < VL * 8; it++) {
                const int idx = it * 32 + lane;
                const int row = idx >> 4, ch = idx & 15;
                cp_async16_hint(vland + row * 256 + ((ch ^ (row & 7)) << 4), P.vc + kv_off + row * DH + ch * 8, pol_first);
            }
            cp_async_commit();
            if (s == 0) {
                const bf16* kp = P.kc + kv_off + (g * DH + t * 8);
#pragma unroll
                for (int i = 0; i < KREG_TILES; i++)
#pragma unroll
                    for (int hh = 0; hh < 2; hh++)
#pragma unroll
                        for (int j = 0; j < 4; j++)
                            ldg128_hint(kreg[i][hh][j], kp + (i * 16 + hh * 8) * DH + j * 32, pol_first);
                if (VPRE > 0 && lane == 0) bulk_prefetch_l2(P.vc + kv_off, VPRE);
            }
            TS2(3);
            __syncthreads();
            mbar_wait(sbase + OFF_XBAR, pass);
            TS2(4);

            float sc[8][2];
            {
                float cacc[KREG_TILES][4];
#pragma unroll
                for (int i = 0; i < KREG_TILES; i++) { cacc[i][0] = cacc[i][1] = cacc[i][2] = cacc[i][3] = 0.f; }
#pragma unroll
                for (int j = 0; j < 4; j++) {
                    const uint4 qv = *reinterpret_cast<const uint4*>(qs + j * 32 + t * 8);
#pragma unroll
                    for (int i = 0; i < KREG_TILES; i++) {
                        mma16816(cacc[i], kreg[i][0][j][0], kreg[i][1][j][0], kreg[i][0][j][1], kreg[i][1][j][1], qv.x, qv.y);
                        mma16816(cacc[i], kreg[i][0][j][2], kreg[i][1][j][2], kreg[i][0][j][3], kreg[i][1][j][3], qv.z, qv.w);
                    }
                }
#pragma unroll
                for (int i = 0; i < KREG_TILES; i++) { sc[i][0] = cacc[i][0]; sc[i][1] = cacc[i][2]; }
            }
            {
                TS2(5);
                if (s == 0) {
                    if (lane == 0) bulk_prefetch_l2(P.vc + kv_off + VL * 16 * DH, (8 - VL) * 4096);
                    cp_async_wait_group<2>();
                    __syncwarp();
                }
                float cacc[KSM_TILES][4];
#pragma unroll
                for (int tt = 0; tt < KSM_TILES; tt++) { cacc[tt][0] = cacc[tt][1] = cacc[tt][2] = cacc[tt][3] = 0.f; }
                const int row0 = (lane & 7) + ((lane >> 3) & 1) * 8;
#pragma unroll 4
                for (int ks = 0; ks < 8; ks++) {
                    const uint32_t b0 = *reinterpret_cast<const uint32_t*>(qs + ks * 16 + 2 * t);
                    const uint32_t b1 = *reinterpret_cast<const uint32_t*>(qs + ks * 16 + 2 * t + 8);
                    const int ch = 2 * ks + (lane >> 4);
                    const uint32_t ad = kb + row0 * 256 + ((ch ^ (lane & 7)) << 4);
#pragma unroll
                    for (int tt = 0; tt < KSM_TILES; tt++) {
                        uint32_t a[4];
                        ldmatrix4(a, ad + tt * 4096);
                        mma16816(cacc[tt], a[0], a[1], a[2], a[3], b0, b1);
                    }
                }
#pragma unroll
                for (int tt = 0; tt < KSM_TILES; tt++) { sc[KREG_TILES + tt][0] = cacc[tt][0]; sc[KREG_TILES + tt][1] = cacc[tt][2]; }
            }
            TS2(6);
            bf16* pw = reinterpret_cast<bf16*>(sm + OFF_P + w * 256);
            {
                float s4[4];
#pragma unroll
                for (int q2 = 0; q2 < 4; q2++) {
                    const int i = q2 >> 1, k2 = q2 & 1;
                    const float v01 = (t & 1) ? sc[2 + i][k2] : sc[i][k2];
                    const float v23 = (t & 1) ? sc[6 + i][k2] : sc[4 + i][k2];
                    s4[q2] = (t & 2) ? v23 : v01;
                }
                float mx = -INFINITY;
#pragma unroll
                for (int q2 = 0; q2 < 4; q2++) {
                    s4[q2] = bf16r(bf16r(s4[q2]) * 0.08838834764831845f);
                    mx = fmaxf(mx, s4[q2]);
                }
#pragma unroll
                for (int o = 1; o < 32; o <<= 1) mx = fmaxf(mx, __shfl_xor_sync(0xffffffffu, mx, o));
                float l = 0.f;
#pragma unroll
                for (int q2 = 0; q2 < 4; q2++) {
                    const bf16 pb = __float2bfloat16_rn(ex2((s4[q2] - mx) * LOG2E));
                    l += __bfloat162float(pb);
                    pw[(2 * t + (q2 >> 1)) * 16 + (q2 & 1) * 8 + g] = pb;
                }
                l = warp_sum(l);
                if (lane == 0) { stat[2 * w] = mx; stat[2 * w + 1] = l; }
            }
            TS2(7);
            __syncthreads();
            TS(2 + s * 6);
            float m_cta = stat[0];
#pragma unroll
            for (int i = 1; i < 8; i++) m_cta = fmaxf(m_cta, stat[2 * i]);
            const float wfac = ex2((stat[2 * w] - m_cta) * LOG2E);
            if (tid == 0) {
                float l_cta = 0.f;
#pragma unroll
                for (int i = 0; i < 8; i++) l_cta += stat[2 * i + 1] * ex2((stat[2 * i] - m_cta) * LOG2E);
                asm volatile("st.relaxed.gpu.global.v4.u32 [%0], {%1,%2,%3,%4};" :: "l"(&g_ml[pass][b]),
                             "r"(__float_as_uint(m_cta)), "r"(__float_as_uint(l_cta)), "r"(epoch * 2 + pass + 1), "r"(0u) : "memory");
            }

            {
                const bf16* vbase = P.vc + kv_off + (4 * t) * DH + g * 8;
                float* ow = oscr + w * 128;
                constexpr int NK = 8 - VL;
                static_assert(NK % NVB == 0, "NVB");
                uint32_t vbuf[NVB][4][4];
#pragma unroll
                for (int u = 0; u < NVB - 1; u++)
#pragma unroll
                    for (int i = 0; i < 4; i++) ldg128_hint(vbuf[u][i], vbase + ((VL + u) * 16 + i) * DH, pol_norm);
                cp_async_wait_all();
                __syncwarp();
#pragma unroll 4
                for (int mt = 0; mt < 8; mt++) {
                    float cl[4] = {0.f, 0.f, 0.f, 0.f};
#pragma unroll
                    for (int kt = 0; kt < VL; kt++) {
                        const uint32_t b0 = *reinterpret_cast<const uint32_t*>(pw + kt * 16 + 2 * t);
                        const uint32_t b1 = *reinterpret_cast<const uint32_t*>(pw + kt * 16 + 2 * t + 8);
                        const int row = kt * 16 + (lane & 7) + ((lane >> 4) & 1) * 8;
                        uint32_t a[4];
                        ldmatrix4t(a, vland + row * 256 + (((2 * mt + ((lane >> 3) & 1)) ^ (lane & 7)) << 4));
                        mma16816(cl, a[0], a[1], a[2], a[3], b0, b1);
                    }
                    if (t == 0) { ow[mt * 16 + g] = cl[0] * wfac; ow[mt * 16 + 8 + g] = cl[2] * wfac; }
                }
                __syncwarp();
                if (w != 7) asm volatile("bar.arrive 1, 256;" ::: "memory");
                float oacc[4][4];
#pragma unroll
                for (int i = 0; i < 4; i++) { oacc[i][0] = oacc[i][1] = oacc[i][2] = oacc[i][3] = 0.f; }
#pragma unroll 1
                for (int hf = 0; hf < 2; hf++) {
#pragma unroll 1
                    for (int k0 = 0; k0 < NK; k0 += NVB) {
                        if (w == 7 && hf == 0 && k0 == NVB) {
                            asm volatile("bar.sync 1, 256;" ::: "memory");
                            if (lane == 0) {
                                mbar_expect_tx(bar_stage, 81920);
#pragma unroll 1
                                for (int i = 0; i < 10; i++) tma_2d_hint(sbase + OFF_STAGE + i * 8192, &tm_wo, i * 64, h * DH + r * 64, bar_stage, pol_first);
                            }
                            __syncwarp();
                        }
#pragma unroll
                        for (int u = 0; u < NVB; u++) {
                            const int kt = k0 + u;
                            int nk = kt + NVB - 1, nh = hf;
                            if (nk >= NK) { nk -= NK; nh = hf + 1; }
                            if (nh < 2) {
                                const bf16* vp = vbase + (VL + nk) * 16 * DH + nh * 64;
#pragma unroll
                                for (int i = 0; i < 4; i++) ldg128_hint(vbuf[(u + NVB - 1) % NVB][i], vp + i * DH, pol_norm);
                            }
                            const uint2 pb = *reinterpret_cast<const uint2*>(pw + (VL + kt) * 16 + 4 * t);
#pragma unroll
                            for (int e = 0; e < 4; e++)
                                mma16816(oacc[e], __byte_perm(vbuf[u][0][e], vbuf[u][1][e], 0x5410), __byte_perm(vbuf[u][0][e], vbuf[u][1][e], 0x7632),
                                         __byte_perm(vbuf[u][2][e], vbuf[u][3][e], 0x5410), __byte_perm(vbuf[u][2][e], vbuf[u][3][e], 0x7632), pb.x, pb.y);
                        }
                    }
                    if (t == 0) {
                        float* o2 = ow + hf * 64 + g * 8;
                        float4 u0 = *reinterpret_cast<float4*>(o2), u1 = *reinterpret_cast<float4*>(o2 + 4);
                        u0.x += oacc[0][0] * wfac; u0.y += oacc[0][2] * wfac; u0.z += oacc[1][0] * wfac; u0.w += oacc[1][2] * wfac;
                        u1.x += oacc[2][0] * wfac; u1.y += oacc[2][2] * wfac; u1.z += oacc[3][0] * wfac; u1.w += oacc[3][2] * wfac;
                        *reinterpret_cast<float4*>(o2) = u0;
                        *reinterpret_cast<float4*>(o2 + 4) = u1;
                    }
#pragma unroll
                    for (int i = 0; i < 4; i++) { oacc[i][0] = oacc[i][1] = oacc[i][2] = oacc[i][3] = 0.f; }
                }
            }
            __syncthreads();
            TS(3 + s * 6);
            TS2(10);
            if (tid < 128) {
                uint4 rec[4];
                {
                    unsigned it = 0;
                    const unsigned tag = epoch * 2 + pass + 1;
                    while (true) {
#pragma unroll
                        for (int i = 0; i < 4; i++)
                            asm volatile("ld.relaxed.gpu.global.v4.u32 {%0,%1,%2,%3}, [%4];"
                                         : "=r"(rec[i].x), "=r"(rec[i].y), "=r"(rec[i].z), "=r"(rec[i].w)
                                         : "l"(&g_ml[pass][(b & ~3) + i]) : "memory");
                        if (rec[0].z == tag && rec[1].z == tag && rec[2].z == tag && rec[3].z == tag) break;
                        if (++it > SPIN_LIMIT) __trap();
                    }
                }
                const float M = fmaxf(fmaxf(__uint_as_float(rec[0].x), __uint_as_float(rec[1].x)),
                                      fmaxf(__uint_as_float(rec[2].x), __uint_as_float(rec[3].x)));
                float L = 0.f;
#pragma unroll
                for (int i = 0; i < 4; i++) L += __uint_as_float(rec[i].y) * ex2((__uint_as_float(rec[i].x) - M) * LOG2E);
                const float scale = __fdividef(ex2((m_cta - M) * LOG2E), L);
                float sum = 0.f;
#pragma unroll
                for (int i = 0; i < 8; i++) sum += oscr[i * 128 + tid];
                if ((tid >> 6) == r) oex[r * 64 + (tid & 63)] = sum * scale;
                else st_async_b32(mapa(sbase + OFF_OEX + (r * 64 + (tid & 63)) * 4, r ^ 1), __float_as_uint(sum * scale), mapa(sbase + OFF_XBAR + 8, r ^ 1));
            }
            TS2(8);
            __syncthreads();
            TS2(9);
            if (tid < 64) {
                mbar_wait(sbase + OFF_XBAR + 8, pass);
                const float o = oex[tid] + oex[64 + tid];
                const bf16 hi = __float2bfloat16_rn(o);
                hs[32 + tid] = hi;
                hs[96 + tid] = __float2bfloat16_rn(o - __bfloat162float(hi));
            }
            mbar_wait(bar_stage, 1);
            __syncthreads();
            TS(4 + s * 6);
            {
                float co[5][4];
#pragma unroll
                for (int i = 0; i < 5; i++) { co[i][0] = co[i][1] = co[i][2] = co[i][3] = 0.f; }
#pragma unroll 1
                for (int ks = 0; ks < 4; ks++) {
                    uint32_t b0 = 0, b1 = 0;
                    if (g < 2) {
                        b0 = *reinterpret_cast<const uint32_t*>(hs + 32 + g * 64 + ks * 16 + 2 * t);
                        b1 = *reinterpret_cast<const uint32_t*>(hs + 32 + g * 64 + ks * 16 + 2 * t + 8);
                    }
                    const int krow = ks * 16 + (lane & 7) + ((lane >> 4) & 1) * 8;
#pragma unroll
                    for (int i = 0; i < 5; i++) {
                        const int ch = 2 * (w * 5 + i) + ((lane >> 3) & 1);
                        uint32_t a[4];
                        ldmatrix4t(a, sbase + OFF_STAGE + (ch >> 3) * 8192 + krow * 128 + (((ch ^ lane) & 7) << 4));
                        mma16816(co[i], a[0], a[1], a[2], a[3], b0, b1);
                    }
                }
                if (t == 0) {
#pragma unroll
                    for (int i = 0; i < 5; i++) {
                        red_add(acc + (w * 5 + i) * 16 + g, co[i][0] + co[i][1]);
                        red_add(acc + (w * 5 + i) * 16 + 8 + g, co[i][2] + co[i][3]);
                    }
                }
            }
            if (s == 0) {
                __syncthreads();
                if (tid == 224) {
                    mbar_expect_tx(bar_stage, 81920);
#pragma unroll 1
                    for (int i = 0; i < 5; i++) tma_2d_hint(sbase + OFF_STAGE + i * 16384, &tm_wq, h * DH + r * 64, i * 128, bar_stage, pol_first);
                }
            }
        } else if (b < MLP_CTAS) {
            {
                float ch4[4] = {0.f, 0.f, 0.f, 0.f};
#pragma unroll
                for (int k5 = 0; k5 < 5; k5++) {
                    const int ks = w * 5 + k5;
                    const uint32_t b0 = *reinterpret_cast<const uint32_t*>(xn + ks * 16 + 2 * t);
                    const uint32_t b1 = *reinterpret_cast<const uint32_t*>(xn + ks * 16 + 2 * t + 8);
                    const int krow = ks * 16 + (lane & 7) + ((lane >> 4) & 1) * 8;
                    uint32_t a[4];
                    ldmatrix4t(a, sbase + OFF_W1 + krow * 32 + ((lane >> 3) & 1) * 16);
                    mma16816(ch4, a[0], a[1], a[2], a[3], b0, b1);
                }
                if (t == 0) { oscr[w * 16 + g] = ch4[0]; oscr[w * 16 + 8 + g] = ch4[2]; }
            }
            __syncthreads();
            if (tid < 16) {
                float sum = 0.f;
#pragma unroll
                for (int i = 0; i < 8; i++) sum += oscr[i * 16 + tid];
                const float u = bf16r(bf16r(sum) + __bfloat162float(hs[16 + tid]));
                const float inner = 0.7978845608028654f * (u + 0.044715f * u * u * u);
                hs[tid] = __float2bfloat16_rn(0.5f * u * (1.0f + tanhf(inner)));
            }
            __syncthreads();
            {
                const uint32_t b0 = *reinterpret_cast<const uint32_t*>(hs + 2 * t);
                const uint32_t b1 = *reinterpret_cast<const uint32_t*>(hs + 2 * t + 8);
                const int krow = (lane & 7) + ((lane >> 4) & 1) * 8;
#pragma unroll
                for (int i = 0; i < 5; i++) {
                    const int ch = 2 * (w * 5 + i) + ((lane >> 3) & 1);
                    uint32_t a[4];
                    float co[4] = {0.f, 0.f, 0.f, 0.f};
                    ldmatrix4t(a, sbase + OFF_W2 + krow * 1280 + ((ch ^ (lane & 7)) << 4));
                    mma16816(co, a[0], a[1], a[2], a[3], b0, b1);
                    if (t == 0) {
                        red_add(acc + (w * 5 + i) * 16 + g, co[0]);
                        red_add(acc + (w * 5 + i) * 16 + 8 + g, co[2]);
                    }
                }
            }
        }
        TS(5 + s * 6);
        TS2(11);
        if (s < 3) grid_barrier(base + NCTA * (s + 1));
        TS(6 + s * 6);
    }
    __syncthreads();
    if (tid == 0) {
        __threadfence();
        const unsigned old = atomicAdd(&g_ctr, 1u);
        s_flag[1] = (old == base + 4 * NCTA - 1) ? 1u : 0u;
        __threadfence();
    }
    __syncthreads();
    if (s_flag[1]) {
        for (int e = tid; e < D_MODEL; e += NT) {
            float a = 0.f;
#pragma unroll
            for (int i = 0; i < NREP; i++) a += __ldcg(&g_acc[3][i][e]);
            const float o = bf16r(bf16r(a) + __bfloat162float(b2s[e]));
            P.out[e] = __float2bfloat16_rn(__bfloat162float(xs[e]) + o);
        }
    }
    TS(25);
}

}

extern "C" void kernel_launch(void* const* d_in, const int* in_sizes, int n_in,
                              void* d_out, int out_size) {
    Params P;
    P.x = (const bf16*)d_in[0];
    P.kc = (const bf16*)d_in[1];
    P.vc = (const bf16*)d_in[2];
    P.wq = (const bf16*)d_in[3];
    P.wo = (const bf16*)d_in[4];
    P.w1 = (const bf16*)d_in[6];
    P.b1 = (const bf16*)d_in[7];
    P.w2 = (const bf16*)d_in[8];
    P.b2 = (const bf16*)d_in[9];
    P.out = (bf16*)d_out;

    cudaFuncSetAttribute(fused_kernel, cudaFuncAttributeMaxDynamicSharedMemorySize, SMEM_BYTES);

    typedef CUresult (*EncodeFn)(CUtensorMap*, CUtensorMapDataType, cuuint32_t, void*, const cuuint64_t*, const cuuint64_t*,
                                 const cuuint32_t*, const cuuint32_t*, CUtensorMapInterleave, CUtensorMapSwizzle,
                                 CUtensorMapL2promotion, CUtensorMapFloatOOBfill);
    void* fn = nullptr;
    cudaDriverEntryPointQueryResult qres;
    cudaGetDriverEntryPoint("cuTensorMapEncodeTiled", &fn, cudaEnableDefault, &qres);
    EncodeFn encode = (EncodeFn)fn;
    CUtensorMap tm_wq, tm_wo;
    {
        cuuint64_t dims[2] = {(cuuint64_t)(NHEAD * DH), (cuuint64_t)D_MODEL};
        cuuint64_t strides[1] = {(cuuint64_t)(NHEAD * DH * 2)};
        cuuint32_t box[2] = {64, 128};
        cuuint32_t es[2] = {1, 1};
        encode(&tm_wq, CU_TENSOR_MAP_DATA_TYPE_BFLOAT16, 2, (void*)P.wq, dims, strides, box, es, CU_TENSOR_MAP_INTERLEAVE_NONE,
               CU_TENSOR_MAP_SWIZZLE_128B, CU_TENSOR_MAP_L2_PROMOTION_NONE, CU_TENSOR_MAP_FLOAT_OOB_FILL_NONE);
    }
    {
        cuuint64_t dims[2] = {(cuuint64_t)D_MODEL, (cuuint64_t)(NHEAD * DH)};
        cuuint64_t strides[1] = {(cuuint64_t)(D_MODEL * 2)};
        cuuint32_t box[2] = {64, 64};
        cuuint32_t es[2] = {1, 1};
        encode(&tm_wo, CU_TENSOR_MAP_DATA_TYPE_BFLOAT16, 2, (void*)P.wo, dims, strides, box, es, CU_TENSOR_MAP_INTERLEAVE_NONE,
               CU_TENSOR_MAP_SWIZZLE_128B, CU_TENSOR_MAP_L2_PROMOTION_NONE, CU_TENSOR_MAP_FLOAT_OOB_FILL_NONE);
    }

    cudaLaunchConfig_t cfg = {};
    cfg.gridDim = dim3(NCTA);
    cfg.blockDim = dim3(NT);
    cfg.dynamicSmemBytes = SMEM_BYTES;
    cfg.stream = cudaStreamPerThread;
    cudaLaunchAttribute at[2];
    at[0].id = cudaLaunchAttributeClusterDimension;
    at[0].val.clusterDim.x = 2; at[0].val.clusterDim.y = 1; at[0].val.clusterDim.z = 1;
    at[1].id = cudaLaunchAttributeCooperative;
    at[1].val.cooperative = 1;
    cfg.attrs = at;
    cfg.numAttrs = 2;
    cudaLaunchKernelEx(&cfg, fused_kernel, P, tm_wq, tm_wo);
}
```

```cpp
#include <cuda_runtime.h>
#include <cuda.h>
#include <cuda_bf16.h>
#include <stdint.h>

typedef __nv_bfloat16 bf16;

namespace {

constexpr int D_MODEL = 640;
constexpr int NHEAD = 32;
constexpr int SEQ = 4096;
constexpr int DH = 128;
constexpr int FF = 1728;
constexpr int NCTA = 128;
constexpr int NT = 256;
constexpr int KREG_TILES = 5;
constexpr int KSM_TILES = 3;
constexpr int MLP_UNITS = 16;
constexpr int MLP_CTAS = FF / MLP_UNITS;

constexpr int OFF_STAGE = 0;
constexpr int OFF_W2 = 81920;
constexpr int OFF_W1 = OFF_W2 + 20480;
constexpr int OFF_K = OFF_W1 + 20480;
constexpr int OFF_XS = OFF_K + 98304;
constexpr int OFF_XN = OFF_XS + 1280;
constexpr int OFF_O = OFF_XN + 1280;
constexpr int OFF_P = OFF_O + 4096;
constexpr int OFF_Q = OFF_P + 2048;
constexpr int OFF_OEX = OFF_Q + 256;
constexpr int OFF_STAT = OFF_OEX + 512;
constexpr int OFF_RED = OFF_STAT + 80;
constexpr int OFF_HS = OFF_RED + 96;
constexpr int OFF_B2 = OFF_HS + 320;
constexpr int OFF_XBAR = OFF_B2 + 1280;
constexpr int SMEM_BYTES = OFF_XBAR + 16;

static_assert(SMEM_BYTES <= 232448, "smem");
#define WOHF 1
#define WOK0 2
#define WOPOL pol_first
#define NREPV 8
constexpr int NREP = NREPV;
constexpr int VL = 2;
#define VPRE 0
#ifndef NVB
#define NVB 2
#endif
constexpr unsigned SPIN_LIMIT = 1u << 24;

__device__ unsigned int g_ctr;
__device__ float g_acc[4][NREP][D_MODEL];
__device__ uint4 g_ml[2][NCTA];

#define TS(i) do {} while (0)
#define TS2(i) do {} while (0)

struct Params {
    const bf16* x; const bf16* kc; const bf16* vc; const bf16* wq; const bf16* wo;
    const bf16* w1; const bf16* b1; const bf16* w2; const bf16* b2; bf16* out;
};

__device__ __forceinline__ float bf16r(float x) { return __bfloat162float(__float2bfloat16_rn(x)); }
__device__ __forceinline__ float bflo(uint32_t u) { return __uint_as_float(u << 16); }
__device__ __forceinline__ float bfhi(uint32_t u) { return __uint_as_float(u & 0xffff0000u); }

__device__ __forceinline__ uint32_t smem_u32(const void* p) { return (uint32_t)__cvta_generic_to_shared(p); }

__device__ __forceinline__ void mbar_init(uint32_t bar, uint32_t cnt) {
    asm volatile("mbarrier.init.shared::cta.b64 [%0], %1;" :: "r"(bar), "r"(cnt) : "memory");
}
__device__ __forceinline__ void mbar_expect_tx(uint32_t bar, uint32_t bytes) {
    asm volatile("mbarrier.arrive.expect_tx.shared::cta.b64 _, [%0], %1;" :: "r"(bar), "r"(bytes) : "memory");
}
__device__ __forceinline__ void mbar_wait(uint32_t bar, uint32_t parity) {
    unsigned it = 0;
    while (true) {
        uint32_t ok;
        asm volatile("{\n\t.reg .pred p;\n\tmbarrier.try_wait.parity.shared::cta.b64 p, [%1], %2;\n\tselp.u32 %0, 1, 0, p;\n\t}"
                     : "=r"(ok) : "r"(bar), "r"(parity) : "memory");
        if (ok) break;
        if (++it > SPIN_LIMIT) __trap();
    }
}
__device__ __forceinline__ void bulk_g2s(uint32_t dst, const void* src, uint32_t bytes, uint32_t bar) {
    asm volatile("cp.async.bulk.shared::cluster.global.mbarrier::complete_tx::bytes [%0], [%1], %2, [%3];"
                 :: "r"(dst), "l"(src), "r"(bytes), "r"(bar) : "memory");
}
__device__ __forceinline__ void bulk_g2s_hint(uint32_t dst, const void* src, uint32_t bytes, uint32_t bar, uint64_t pol) {
    asm volatile("cp.async.bulk.shared::cluster.global.mbarrier::complete_tx::bytes.L2::cache_hint [%0], [%1], %2, [%3], %4;"
                 :: "r"(dst), "l"(src), "r"(bytes), "r"(bar), "l"(pol) : "memory");
}
__device__ __forceinline__ void tma_2d_hint(uint32_t dst, const CUtensorMap* tm, int c0, int c1, uint32_t bar, uint64_t pol) {
    asm volatile("cp.async.bulk.tensor.2d.shared::cluster.global.mbarrier::complete_tx::bytes.L2::cache_hint [%0], [%1, {%3, %4}], [%2], %5;"
                 :: "r"(dst), "l"(tm), "r"(bar), "r"(c0), "r"(c1), "l"(pol) : "memory");
}
__device__ __forceinline__ void bulk_prefetch_l2(const void* src, uint32_t bytes) {
    asm volatile("cp.async.bulk.prefetch.L2.global [%0], %1;" :: "l"(src), "r"(bytes) : "memory");
}
__device__ __forceinline__ void bulk_prefetch_l2_hint(const void* src, uint32_t bytes, uint64_t pol) {
    asm volatile("cp.async.bulk.prefetch.L2.global.L2::cache_hint [%0], %1, %2;" :: "l"(src), "r"(bytes), "l"(pol) : "memory");
}
__device__ __forceinline__ float ex2(float x) { float y; asm("ex2.approx.ftz.f32 %0, %1;" : "=f"(y) : "f"(x)); return y; }
__device__ __forceinline__ void cp_async16_hint(uint32_t dst, const void* src, uint64_t pol) {
    asm volatile("cp.async.cg.shared.global.L2::cache_hint [%0], [%1], 16, %2;" :: "r"(dst), "l"(src), "l"(pol) : "memory");
}
__device__ __forceinline__ void cp_async_wait_all() { asm volatile("cp.async.wait_all;" ::: "memory"); }
__device__ __forceinline__ void cp_async_commit() { asm volatile("cp.async.commit_group;" ::: "memory"); }
template <int N> __device__ __forceinline__ void cp_async_wait_group() { asm volatile("cp.async.wait_group %0;" :: "n"(N) : "memory"); }

__device__ __forceinline__ void ldg128_hint(uint32_t (&r)[4], const void* p, uint64_t pol) {
    asm volatile("ld.global.nc.L1::no_allocate.L2::cache_hint.v4.u32 {%0,%1,%2,%3}, [%4], %5;"
                 : "=r"(r[0]), "=r"(r[1]), "=r"(r[2]), "=r"(r[3]) : "l"(p), "l"(pol));
}
__device__ __forceinline__ void ldg128(uint32_t (&r)[4], const void* p) {
    asm volatile("ld.global.nc.v4.u32 {%0,%1,%2,%3}, [%4];"
                 : "=r"(r[0]), "=r"(r[1]), "=r"(r[2]), "=r"(r[3]) : "l"(p));
}
__device__ __forceinline__ void mma16816(float (&c)[4], uint32_t a0, uint32_t a1, uint32_t a2, uint32_t a3,
                                         uint32_t b0, uint32_t b1) {
    asm volatile("mma.sync.aligned.m16n8k16.row.col.f32.bf16.bf16.f32 {%0,%1,%2,%3}, {%4,%5,%6,%7}, {%8,%9}, {%0,%1,%2,%3};"
                 : "+f"(c[0]), "+f"(c[1]), "+f"(c[2]), "+f"(c[3])
                 : "r"(a0), "r"(a1), "r"(a2), "r"(a3), "r"(b0), "r"(b1));
}
__device__ __forceinline__ void ldmatrix4(uint32_t (&r)[4], uint32_t addr) {
    asm volatile("ldmatrix.sync.aligned.m8n8.x4.shared.b16 {%0,%1,%2,%3}, [%4];"
                 : "=r"(r[0]), "=r"(r[1]), "=r"(r[2]), "=r"(r[3]) : "r"(addr) : "memory");
}
__device__ __forceinline__ void red_add_v4(float* p, float a, float b, float c, float d) {
    asm volatile("red.global.add.v4.f32 [%0], {%1,%2,%3,%4};" :: "l"(p), "f"(a), "f"(b), "f"(c), "f"(d) : "memory");
}
__device__ __forceinline__ unsigned ld_acquire(const unsigned* p) {
    unsigned v; asm volatile("ld.acquire.gpu.global.u32 %0, [%1];" : "=r"(v) : "l"(p) : "memory"); return v;
}
__device__ __forceinline__ void st_release(unsigned* p, unsigned v) {
    asm volatile("st.release.gpu.global.u32 [%0], %1;" :: "l"(p), "r"(v) : "memory");
}
__device__ __forceinline__ void cluster_sync_all() {
    asm volatile("barrier.cluster.arrive.release.aligned;\n\tbarrier.cluster.wait.acquire.aligned;" ::: "memory");
}
__device__ __forceinline__ uint32_t mapa(uint32_t addr, uint32_t rank) {
    uint32_t r; asm volatile("mapa.shared::cluster.u32 %0, %1, %2;" : "=r"(r) : "r"(addr), "r"(rank)); return r;
}
__device__ __forceinline__ void st_async_b32(uint32_t addr, uint32_t v, uint32_t bar) {
    asm volatile("st.async.weak.shared::cluster.mbarrier::complete_tx::bytes.b32 [%0], %1, [%2];" :: "r"(addr), "r"(v), "r"(bar) : "memory");
}
__device__ __forceinline__ void st_cluster_f32(uint32_t addr, float v) {
    asm volatile("st.shared::cluster.f32 [%0], %1;" :: "r"(addr), "f"(v) : "memory");
}
__device__ __forceinline__ void st_cluster_u16(uint32_t addr, uint16_t v) {
    asm volatile("st.shared::cluster.u16 [%0], %1;" :: "r"(addr), "h"(v) : "memory");
}
__device__ __forceinline__ float warp_sum(float v) {
#pragma unroll
    for (int o = 16; o > 0; o >>= 1) v += __shfl_xor_sync(0xffffffffu, v, o);
    return v;
}

__device__ __forceinline__ void grid_barrier(unsigned target) {
    __syncthreads();
    if (threadIdx.x == 0) {
        __threadfence();
        atomicAdd(&g_ctr, 1u);
        unsigned it = 0;
        while ((int)(ld_acquire(&g_ctr) - target) < 0) { if (++it > SPIN_LIMIT) __trap(); }
    }
    __syncthreads();
}

constexpr float LOG2E = 1.4426950408889634f;

__device__ __forceinline__ void ldmatrix4t(uint32_t (&r)[4], uint32_t addr) {
    asm volatile("ldmatrix.sync.aligned.m8n8.x4.trans.shared.b16 {%0,%1,%2,%3}, [%4];"
                 : "=r"(r[0]), "=r"(r[1]), "=r"(r[2]), "=r"(r[3]) : "r"(addr) : "memory");
}
__device__ __forceinline__ void red_add(float* p, float a) {
    asm volatile("red.global.add.f32 [%0], %1;" :: "l"(p), "f"(a) : "memory");
}
__device__ __forceinline__ uint32_t pack_bf16(float lo, float hi) {
    uint32_t r; asm("cvt.rn.bf16x2.f32 %0, %1, %2;" : "=r"(r) : "f"(hi), "f"(lo)); return r;
}

__global__ void __launch_bounds__(NT, 1) fused_kernel(const Params P, const __grid_constant__ CUtensorMap tm_wq,
                                                        const __grid_constant__ CUtensorMap tm_wo) {
    extern __shared__ __align__(1024) unsigned char sm[];
    const int tid = threadIdx.x, lane = tid & 31, w = tid >> 5;
    const int g = lane >> 2, t = lane & 3;
    const int b = blockIdx.x, h = b >> 2, c = b & 3, r = b & 1;
    const uint32_t sbase = smem_u32(sm);
    bf16* xs = reinterpret_cast<bf16*>(sm + OFF_XS);
    bf16* xn = reinterpret_cast<bf16*>(sm + OFF_XN);
    bf16* b2s = reinterpret_cast<bf16*>(sm + OFF_B2);
    float* oscr = reinterpret_cast<float*>(sm + OFF_O);
    bf16* qs = reinterpret_cast<bf16*>(sm + OFF_Q);
    float* oex = reinterpret_cast<float*>(sm + OFF_OEX);
    float* stat = reinterpret_cast<float*>(sm + OFF_STAT);
    float* red = reinterpret_cast<float*>(sm + OFF_RED);
    bf16* hs = reinterpret_cast<bf16*>(sm + OFF_HS);
    volatile unsigned* s_flag = reinterpret_cast<volatile unsigned*>(sm + OFF_STAT + 64);
    const uint32_t bar_stage = sbase + OFF_STAT + 72;

    TS(0);
    if (tid < D_MODEL / 8) *reinterpret_cast<uint4*>(xs + tid * 8) = __ldg(reinterpret_cast<const uint4*>(P.x) + tid);
    else if (tid < D_MODEL / 4) *reinterpret_cast<uint4*>(b2s + (tid - 80) * 8) = __ldg(reinterpret_cast<const uint4*>(P.b2) + (tid - 80));
    else if (tid < 162) { if (b < MLP_CTAS) *reinterpret_cast<uint4*>(hs + 16 + (tid - 160) * 8) = __ldg(reinterpret_cast<const uint4*>(P.b1 + b * MLP_UNITS) + (tid - 160)); }
    else if (tid == 192) s_flag[0] = ld_acquire(&g_ctr) >> 9;
    uint64_t pol_first;
    asm volatile("createpolicy.fractional.L2::evict_first.b64 %0, 1.0;" : "=l"(pol_first));
    uint64_t pol_norm;
    asm volatile("createpolicy.fractional.L2::evict_normal.b64 %0, 1.0;" : "=l"(pol_norm));

    const size_t kv_off = (size_t)(h * SEQ + c * 1024 + w * 128) * DH;
    if (tid == 224) {
        mbar_init(bar_stage, 1);
        mbar_init(sbase + OFF_XBAR, 1);
        mbar_init(sbase + OFF_XBAR + 8, 1);
        asm volatile("fence.mbarrier_init.release.cluster;" ::: "memory");
        asm volatile("fence.proxy.async.shared::cta;" ::: "memory");
        mbar_expect_tx(bar_stage, 81920);
#pragma unroll
        for (int i = 0; i < 5; i++) tma_2d_hint(sbase + OFF_STAGE + i * 16384, &tm_wq, h * DH + r * 64, i * 128, bar_stage, pol_first);
    }
    const uint32_t kb = sbase + OFF_K + w * (KSM_TILES * 16 * 256);
    {
        const bf16* kq = P.kc + kv_off + KREG_TILES * 16 * DH;
#pragma unroll 1
        for (int it = 0; it < KSM_TILES * 8; it++) {
            const int idx = it * 32 + lane;
            const int row = idx >> 4, ch = idx & 15;
            cp_async16_hint(kb + row * 256 + ((ch ^ (row & 7)) << 4), kq + row * DH + ch * 8, pol_first);
        }
    }
    cp_async_commit();
    if (b < MLP_CTAS) {
#pragma unroll 1
        for (int idx = tid; idx < 2 * D_MODEL; idx += NT) {
            const int row = idx >> 1, hf = idx & 1;
            cp_async16_hint(sbase + OFF_W1 + row * 32 + hf * 16, P.w1 + (size_t)row * FF + b * MLP_UNITS + hf * 8, pol_first);
            const int r2 = idx / 80, ch = idx - r2 * 80;
            cp_async16_hint(sbase + OFF_W2 + r2 * 1280 + ((ch ^ (r2 & 7)) << 4), P.w2 + (size_t)(b * MLP_UNITS) * D_MODEL + idx * 8, pol_first);
        }
    }
    cp_async_commit();
    if (b == 1) for (int e = tid; e < 3 * NREP * D_MODEL; e += NT) (&g_acc[1][0][0])[e] = 0.f;
    uint32_t kreg[KREG_TILES][2][4][4];
    __syncthreads();
    asm volatile("barrier.cluster.arrive.relaxed.aligned;" ::: "memory");
    const unsigned epoch = s_flag[0];
    const unsigned base = epoch << 9;

#pragma unroll 1
    for (int s = 0; s < 4; s++) {
        {
            float v[4] = {0.f, 0.f, 0.f, 0.f};
            if (tid < D_MODEL / 4) {
                const uint2 xr = *reinterpret_cast<const uint2*>(xs + tid * 4);
                v[0] = bflo(xr.x); v[1] = bfhi(xr.x); v[2] = bflo(xr.y); v[3] = bfhi(xr.y);
                if (s != 0) {
                    float4 a = __ldcg(reinterpret_cast<const float4*>(&g_acc[s - 1][0][0]) + tid);
#pragma unroll
                    for (int i = 1; i < NREP; i++) {
                        const float4 a2 = __ldcg(reinterpret_cast<const float4*>(&g_acc[s - 1][i][0]) + tid);
                        a.x += a2.x; a.y += a2.y; a.z += a2.z; a.w += a2.w;
                    }
                    a.x = bf16r(a.x); a.y = bf16r(a.y); a.z = bf16r(a.z); a.w = bf16r(a.w);
                    if (s == 2) {
                        const uint2 br = *reinterpret_cast<const uint2*>(b2s + tid * 4);
                        a.x = bf16r(a.x + bflo(br.x)); a.y = bf16r(a.y + bfhi(br.x));
                        a.z = bf16r(a.z + bflo(br.y)); a.w = bf16r(a.w + bfhi(br.y));
                    }
                    v[0] = bf16r(v[0] + a.x); v[1] = bf16r(v[1] + a.y); v[2] = bf16r(v[2] + a.z); v[3] = bf16r(v[3] + a.w);
                    *reinterpret_cast<uint2*>(xs + tid * 4) = make_uint2(pack_bf16(v[0], v[1]), pack_bf16(v[2], v[3]));
                }
            }
            if (s == 2 && b == 0) {
                for (int e = tid; e < NREP * D_MODEL; e += NT) (&g_acc[0][0][0])[e] = 0.f;
            }
#pragma unroll 1
            for (int rep = 0; rep <= (s & 1); rep++) {
                float mean = 0.25f * ((v[0] + v[1]) + (v[2] + v[3]));
                float m2 = (v[0] - mean) * (v[0] - mean) + (v[1] - mean) * (v[1] - mean) +
                           (v[2] - mean) * (v[2] - mean) + (v[3] - mean) * (v[3] - mean);
                float hn = 2.f;
#pragma unroll
                for (int o = 1; o < 32; o <<= 1) {
                    const float mo = __shfl_xor_sync(0xffffffffu, mean, o);
                    const float qo = __shfl_xor_sync(0xffffffffu, m2, o);
                    const float d = mo - mean;
                    m2 = m2 + qo + d * d * hn;
                    mean = 0.5f * (mean + mo);
                    hn *= 2.f;
                }
                float* rd = red + rep * 12;
                if (lane == 0 && w < 5) { rd[2 * w] = mean; rd[2 * w + 1] = m2; }
                __syncthreads();
                float gm = 0.f, gq = 0.f;
#pragma unroll
                for (int i = 0; i < 5; i++) { gm += rd[2 * i]; gq += rd[2 * i + 1]; }
                gm *= 0.2f;
#pragma unroll
                for (int i = 0; i < 5; i++) { const float d = rd[2 * i] - gm; gq += 128.f * d * d; }
                const float mb = bf16r(gm);
                const float den = bf16r(sqrtf(bf16r(bf16r(gq * (1.0f / D_MODEL)) + 1e-5f)));
#pragma unroll
                for (int i = 0; i < 4; i++) v[i] = bf16r(__fdividef(bf16r(v[i] - mb), den));
            }
            if (tid < D_MODEL / 4)
                *reinterpret_cast<uint2*>(xn + tid * 4) = make_uint2(pack_bf16(v[0], v[1]), pack_bf16(v[2], v[3]));
        }
        if (s == 1) cp_async_wait_all();
        __syncthreads();
        TS(1 + s * 6);
        TS2(0);
        float* acc = &g_acc[s][b & (NREP - 1)][0];

        if (!(s & 1)) {
            const int pass = s >> 1;
            mbar_wait(bar_stage, 0);
            {
                float cq[4][4];
#pragma unroll
                for (int i = 0; i < 4; i++) { cq[i][0] = cq[i][1] = cq[i][2] = cq[i][3] = 0.f; }
#pragma unroll
                for (int k5 = 0; k5 < 5; k5++) {
                    const int ks = w * 5 + k5;
                    const uint32_t b0 = *reinterpret_cast<const uint32_t*>(xn + ks * 16 + 2 * t);
                    const uint32_t b1 = *reinterpret_cast<const uint32_t*>(xn + ks * 16 + 2 * t + 8);
                    const int krow = ks * 16 + (lane & 7) + ((lane >> 4) & 1) * 8;
#pragma unroll
                    for (int mt = 0; mt < 4; mt++) {
                        uint32_t a[4];
                        ldmatrix4t(a, sbase + OFF_STAGE + krow * 128 + (((2 * mt + ((lane >> 3) & 1)) ^ (lane & 7)) << 4));
                        mma16816(cq[mt], a[0], a[1], a[2], a[3], b0, b1);
                    }
                }
                if (t == 0) {
#pragma unroll
                    for (int mt = 0; mt < 4; mt++) { oscr[w * 64 + mt * 16 + g] = cq[mt][0]; oscr[w * 64 + mt * 16 + 8 + g] = cq[mt][2]; }
                }
            }
            TS2(1);
            __syncthreads();
            TS2(2);
            if (s == 0) asm volatile("barrier.cluster.wait.aligned;" ::: "memory");
            if (tid < 32) {
                float s0 = 0.f, s1 = 0.f;
#pragma unroll
                for (int i = 0; i < 8; i++) { const float2 v2 = *reinterpret_cast<const float2*>(oscr + i * 64 + 2 * tid); s0 += v2.x; s1 += v2.y; }
                const uint32_t qp = pack_bf16(s0, s1);
                *reinterpret_cast<uint32_t*>(qs + r * 64 + 2 * tid) = qp;
                st_async_b32(mapa(sbase + OFF_Q + (r * 64 + 2 * tid) * 2, r ^ 1), qp, mapa(sbase + OFF_XBAR, r ^ 1));
                if (tid == 0) { mbar_expect_tx(sbase + OFF_XBAR, 128); mbar_expect_tx(sbase + OFF_XBAR + 8, 256); }
            }
            const uint32_t vland = sbase + OFF_STAGE + w * (VL * 4096);
#pragma unroll 1
            for (int it = 0; it < VL * 8; it++) {
                const int idx = it * 32 + lane;
                const int row = idx >> 4, ch = idx & 15;
                cp_async16_hint(vland + row * 256 + ((ch ^ (row & 7)) << 4), P.vc + kv_off + row * DH + ch * 8, pol_first);
            }
            cp_async_commit();
            if (s == 0) {
                const bf16* kp = P.kc + kv_off + (g * DH + t * 8);
#pragma unroll
                for (int i = 0; i < KREG_TILES; i++)
#pragma unroll
                    for (int hh = 0; hh < 2; hh++)
#pragma unroll
                        for (int j = 0; j < 4; j++)
                            ldg128_hint(kreg[i][hh][j], kp + (i * 16 + hh * 8) * DH + j * 32, pol_first);
                if (VPRE > 0 && lane == 0) bulk_prefetch_l2(P.vc + kv_off, VPRE);
            }
            TS2(3);
            __syncthreads();
            mbar_wait(sbase + OFF_XBAR, pass);
            TS2(4);

            float sc[8][2];
            {
                float cacc[KREG_TILES][4];
#pragma unroll
                for (int i = 0; i < KREG_TILES; i++) { cacc[i][0] = cacc[i][1] = cacc[i][2] = cacc[i][3] = 0.f; }
#pragma unroll
                for (int j = 0; j < 4; j++) {
                    const uint4 qv = *reinterpret_cast<const uint4*>(qs + j * 32 + t * 8);
#pragma unroll
                    for (int i = 0; i < KREG_TILES; i++) {
                        mma16816(cacc[i], kreg[i][0][j][0], kreg[i][1][j][0], kreg[i][0][j][1], kreg[i][1][j][1], qv.x, qv.y);
                        mma16816(cacc[i], kreg[i][0][j][2], kreg[i][1][j][2], kreg[i][0][j][3], kreg[i][1][j][3], qv.z, qv.w);
                    }
                }
#pragma unroll
                for (int i = 0; i < KREG_TILES; i++) { sc[i][0] = cacc[i][0]; sc[i][1] = cacc[i][2]; }
            }
            {
                TS2(5);
                if (s == 0) {
                    if (lane == 0) bulk_prefetch_l2(P.vc + kv_off + VL * 16 * DH, (8 - VL) * 4096);
                    cp_async_wait_group<2>();
                    __syncwarp();
                }
                float cacc[KSM_TILES][4];
#pragma unroll
                for (int tt = 0; tt < KSM_TILES; tt++) { cacc[tt][0] = cacc[tt][1] = cacc[tt][2] = cacc[tt][3] = 0.f; }
                const int row0 = (lane & 7) + ((lane >> 3) & 1) * 8;
#pragma unroll 4
                for (int ks = 0; ks < 8; ks++) {
                    const uint32_t b0 = *reinterpret_cast<const uint32_t*>(qs + ks * 16 + 2 * t);
                    const uint32_t b1 = *reinterpret_cast<const uint32_t*>(qs + ks * 16 + 2 * t + 8);
                    const int ch = 2 * ks + (lane >> 4);
                    const uint32_t ad = kb + row0 * 256 + ((ch ^ (lane & 7)) << 4);
#pragma unroll
                    for (int tt = 0; tt < KSM_TILES; tt++) {
                        uint32_t a[4];
                        ldmatrix4(a, ad + tt * 4096);
                        mma16816(cacc[tt], a[0], a[1], a[2], a[3], b0, b1);
                    }
                }
#pragma unroll
                for (int tt = 0; tt < KSM_TILES; tt++) { sc[KREG_TILES + tt][0] = cacc[tt][0]; sc[KREG_TILES + tt][1] = cacc[tt][2]; }
            }
            TS2(6);
            bf16* pw = reinterpret_cast<bf16*>(sm + OFF_P + w * 256);
            {
                float s4[4];
#pragma unroll
                for (int q2 = 0; q2 < 4; q2++) {
                    const int i = q2 >> 1, k2 = q2 & 1;
                    const float v01 = (t & 1) ? sc[2 + i][k2] : sc[i][k2];
                    const float v23 = (t & 1) ? sc[6 + i][k2] : sc[4 + i][k2];
                    s4[q2] = (t & 2) ? v23 : v01;
                }
                float mx = -INFINITY;
#pragma unroll
                for (int q2 = 0; q2 < 4; q2++) {
                    s4[q2] = bf16r(bf16r(s4[q2]) * 0.08838834764831845f);
                    mx = fmaxf(mx, s4[q2]);
                }
#pragma unroll
                for (int o = 1; o < 32; o <<= 1) mx = fmaxf(mx, __shfl_xor_sync(0xffffffffu, mx, o));
                float l = 0.f;
#pragma unroll
                for (int q2 = 0; q2 < 4; q2++) {
                    const bf16 pb = __float2bfloat16_rn(ex2((s4[q2] - mx) * LOG2E));
                    l += __bfloat162float(pb);
                    pw[(2 * t + (q2 >> 1)) * 16 + (q2 & 1) * 8 + g] = pb;
                }
                l = warp_sum(l);
                if (lane == 0) { stat[2 * w] = mx; stat[2 * w + 1] = l; }
            }
            TS2(7);
            __syncthreads();
            TS(2 + s * 6);
            float m_cta = stat[0];
#pragma unroll
            for (int i = 1; i < 8; i++) m_cta = fmaxf(m_cta, stat[2 * i]);
            const float wfac = ex2((stat[2 * w] - m_cta) * LOG2E);
            if (tid == 0) {
                float l_cta = 0.f;
#pragma unroll
                for (int i = 0; i < 8; i++) l_cta += stat[2 * i + 1] * ex2((stat[2 * i] - m_cta) * LOG2E);
                asm volatile("st.relaxed.gpu.global.v4.u32 [%0], {%1,%2,%3,%4};" :: "l"(&g_ml[pass][b]),
                             "r"(__float_as_uint(m_cta)), "r"(__float_as_uint(l_cta)), "r"(epoch * 2 + pass + 1), "r"(0u) : "memory");
            }

            {
                const bf16* vbase = P.vc + kv_off + (4 * t) * DH + g * 8;
                float* ow = oscr + w * 128;
                constexpr int NK = 8 - VL;
                static_assert(NK % NVB == 0, "NVB");
                uint32_t vbuf[NVB][4][4];
#pragma unroll
                for (int u = 0; u < NVB - 1; u++)
#pragma unroll
                    for (int i = 0; i < 4; i++) ldg128_hint(vbuf[u][i], vbase + ((VL + u) * 16 + i) * DH, pol_norm);
                cp_async_wait_all();
                __syncwarp();
#pragma unroll 4
                for (int mt = 0; mt < 8; mt++) {
                    float cl[4] = {0.f, 0.f, 0.f, 0.f};
#pragma unroll
                    for (int kt = 0; kt < VL; kt++) {
                        const uint32_t b0 = *reinterpret_cast<const uint32_t*>(pw + kt * 16 + 2 * t);
                        const uint32_t b1 = *reinterpret_cast<const uint32_t*>(pw + kt * 16 + 2 * t + 8);
                        const int row = kt * 16 + (lane & 7) + ((lane >> 4) & 1) * 8;
                        uint32_t a[4];
                        ldmatrix4t(a, vland + row * 256 + (((2 * mt + ((lane >> 3) & 1)) ^ (lane & 7)) << 4));
                        mma16816(cl, a[0], a[1], a[2], a[3], b0, b1);
                    }
                    if (t == 0) { ow[mt * 16 + g] = cl[0] * wfac; ow[mt * 16 + 8 + g] = cl[2] * wfac; }
                }
                __syncwarp();
                if (w != 7) asm volatile("bar.arrive 1, 256;" ::: "memory");
                float oacc[4][4];
#pragma unroll
                for (int i = 0; i < 4; i++) { oacc[i][0] = oacc[i][1] = oacc[i][2] = oacc[i][3] = 0.f; }
#pragma unroll 1
                for (int hf = 0; hf < 2; hf++) {
#pragma unroll 1
                    for (int k0 = 0; k0 < NK; k0 += NVB) {
                        if (w == 7 && hf == WOHF && k0 == WOK0) {
                            asm volatile("bar.sync 1, 256;" ::: "memory");
                            if (lane == 0) {
                                mbar_expect_tx(bar_stage, 81920);
#pragma unroll 1
                                for (int i = 0; i < 10; i++) tma_2d_hint(sbase + OFF_STAGE + i * 8192, &tm_wo, i * 64, h * DH + r * 64, bar_stage, WOPOL);
                            }
                            __syncwarp();
                        }
#pragma unroll
                        for (int u = 0; u < NVB; u++) {
                            const int kt = k0 + u;
                            int nk = kt + NVB - 1, nh = hf;
                            if (nk >= NK) { nk -= NK; nh = hf + 1; }
                            if (nh < 2) {
                                const bf16* vp = vbase + (VL + nk) * 16 * DH + nh * 64;
#pragma unroll
                                for (int i = 0; i < 4; i++) ldg128_hint(vbuf[(u + NVB - 1) % NVB][i], vp + i * DH, pol_norm);
                            }
                            const uint2 pb = *reinterpret_cast<const uint2*>(pw + (VL + kt) * 16 + 4 * t);
#pragma unroll
                            for (int e = 0; e < 4; e++)
                                mma16816(oacc[e], __byte_perm(vbuf[u][0][e], vbuf[u][1][e], 0x5410), __byte_perm(vbuf[u][0][e], vbuf[u][1][e], 0x7632),
                                         __byte_perm(vbuf[u][2][e], vbuf[u][3][e], 0x5410), __byte_perm(vbuf[u][2][e], vbuf[u][3][e], 0x7632), pb.x, pb.y);
                        }
                    }
                    if (t == 0) {
                        float* o2 = ow + hf * 64 + g * 8;
                        float4 u0 = *reinterpret_cast<float4*>(o2), u1 = *reinterpret_cast<float4*>(o2 + 4);
                        u0.x += oacc[0][0] * wfac; u0.y += oacc[0][2] * wfac; u0.z += oacc[1][0] * wfac; u0.w += oacc[1][2] * wfac;
                        u1.x += oacc[2][0] * wfac; u1.y += oacc[2][2] * wfac; u1.z += oacc[3][0] * wfac; u1.w += oacc[3][2] * wfac;
                        *reinterpret_cast<float4*>(o2) = u0;
                        *reinterpret_cast<float4*>(o2 + 4) = u1;
                    }
#pragma unroll
                    for (int i = 0; i < 4; i++) { oacc[i][0] = oacc[i][1] = oacc[i][2] = oacc[i][3] = 0.f; }
                }
            }
            __syncthreads();
            TS(3 + s * 6);
            TS2(10);
            if (tid < 128) {
                uint4 rec[4];
                {
                    unsigned it = 0;
                    const unsigned tag = epoch * 2 + pass + 1;
                    while (true) {
#pragma unroll
                        for (int i = 0; i < 4; i++)
                            asm volatile("ld.relaxed.gpu.global.v4.u32 {%0,%1,%2,%3}, [%4];"
                                         : "=r"(rec[i].x), "=r"(rec[i].y), "=r"(rec[i].z), "=r"(rec[i].w)
                                         : "l"(&g_ml[pass][(b & ~3) + i]) : "memory");
                        if (rec[0].z == tag && rec[1].z == tag && rec[2].z == tag && rec[3].z == tag) break;
                        if (++it > SPIN_LIMIT) __trap();
                    }
                }
                const float M = fmaxf(fmaxf(__uint_as_float(rec[0].x), __uint_as_float(rec[1].x)),
                                      fmaxf(__uint_as_float(rec[2].x), __uint_as_float(rec[3].x)));
                float L = 0.f;
#pragma unroll
                for (int i = 0; i < 4; i++) L += __uint_as_float(rec[i].y) * ex2((__uint_as_float(rec[i].x) - M) * LOG2E);
                const float scale = __fdividef(ex2((m_cta - M) * LOG2E), L);
                float sum = 0.f;
#pragma unroll
                for (int i = 0; i < 8; i++) sum += oscr[i * 128 + tid];
                if ((tid >> 6) == r) oex[r * 64 + (tid & 63)] = sum * scale;
                else st_async_b32(mapa(sbase + OFF_OEX + (r * 64 + (tid & 63)) * 4, r ^ 1), __float_as_uint(sum * scale), mapa(sbase + OFF_XBAR + 8, r ^ 1));
            }
            TS2(8);
            __syncthreads();
            TS2(9);
            if (tid < 64) {
                mbar_wait(sbase + OFF_XBAR + 8, pass);
                const float o = oex[tid] + oex[64 + tid];
                const bf16 hi = __float2bfloat16_rn(o);
                hs[32 + tid] = hi;
                hs[96 + tid] = __float2bfloat16_rn(o - __bfloat162float(hi));
            }
            mbar_wait(bar_stage, 1);
            __syncthreads();
            TS(4 + s * 6);
            {
                float co[5][4];
#pragma unroll
                for (int i = 0; i < 5; i++) { co[i][0] = co[i][1] = co[i][2] = co[i][3] = 0.f; }
#pragma unroll 1
                for (int ks = 0; ks < 4; ks++) {
                    uint32_t b0 = 0, b1 = 0;
                    if (g < 2) {
                        b0 = *reinterpret_cast<const uint32_t*>(hs + 32 + g * 64 + ks * 16 + 2 * t);
                        b1 = *reinterpret_cast<const uint32_t*>(hs + 32 + g * 64 + ks * 16 + 2 * t + 8);
                    }
                    const int krow = ks * 16 + (lane & 7) + ((lane >> 4) & 1) * 8;
#pragma unroll
                    for (int i = 0; i < 5; i++) {
                        const int ch = 2 * (w * 5 + i) + ((lane >> 3) & 1);
                        uint32_t a[4];
                        ldmatrix4t(a, sbase + OFF_STAGE + (ch >> 3) * 8192 + krow * 128 + (((ch ^ lane) & 7) << 4));
                        mma16816(co[i], a[0], a[1], a[2], a[3], b0, b1);
                    }
                }
                if (t == 0) {
#pragma unroll
                    for (int i = 0; i < 5; i++) {
                        oscr[(w * 5 + i) * 16 + g] = co[i][0] + co[i][1];
                        oscr[(w * 5 + i) * 16 + 8 + g] = co[i][2] + co[i][3];
                    }
                }
                __syncwarp();
                if (lane < 20) {
                    const float4 v4 = *reinterpret_cast<const float4*>(oscr + w * 80 + lane * 4);
                    red_add_v4(acc + w * 80 + lane * 4, v4.x, v4.y, v4.z, v4.w);
                }
            }
            if (s == 0) {
                __syncthreads();
                if (tid == 224) {
                    mbar_expect_tx(bar_stage, 81920);
#pragma unroll 1
                    for (int i = 0; i < 5; i++) tma_2d_hint(sbase + OFF_STAGE + i * 16384, &tm_wq, h * DH + r * 64, i * 128, bar_stage, pol_first);
                }
            }
        } else if (b < MLP_CTAS) {
            {
                float ch4[4] = {0.f, 0.f, 0.f, 0.f};
#pragma unroll
                for (int k5 = 0; k5 < 5; k5++) {
                    const int ks = w * 5 + k5;
                    const uint32_t b0 = *reinterpret_cast<const uint32_t*>(xn + ks * 16 + 2 * t);
                    const uint32_t b1 = *reinterpret_cast<const uint32_t*>(xn + ks * 16 + 2 * t + 8);
                    const int krow = ks * 16 + (lane & 7) + ((lane >> 4) & 1) * 8;
                    uint32_t a[4];
                    ldmatrix4t(a, sbase + OFF_W1 + krow * 32 + ((lane >> 3) & 1) * 16);
                    mma16816(ch4, a[0], a[1], a[2], a[3], b0, b1);
                }
                if (t == 0) { oscr[w * 16 + g] = ch4[0]; oscr[w * 16 + 8 + g] = ch4[2]; }
            }
            __syncthreads();
            if (tid < 16) {
                float sum = 0.f;
#pragma unroll
                for (int i = 0; i < 8; i++) sum += oscr[i * 16 + tid];
                const float u = bf16r(bf16r(sum) + __bfloat162float(hs[16 + tid]));
                const float inner = 0.7978845608028654f * (u + 0.044715f * u * u * u);
                const float th = 1.0f - __fdividef(2.0f, ex2(inner * (2.0f * LOG2E)) + 1.0f);
                hs[tid] = __float2bfloat16_rn(0.5f * u * (1.0f + th));
            }
            __syncthreads();
            {
                const uint32_t b0 = *reinterpret_cast<const uint32_t*>(hs + 2 * t);
                const uint32_t b1 = *reinterpret_cast<const uint32_t*>(hs + 2 * t + 8);
                const int krow = (lane & 7) + ((lane >> 4) & 1) * 8;
#pragma unroll
                for (int i = 0; i < 5; i++) {
                    const int ch = 2 * (w * 5 + i) + ((lane >> 3) & 1);
                    uint32_t a[4];
                    float co[4] = {0.f, 0.f, 0.f, 0.f};
                    ldmatrix4t(a, sbase + OFF_W2 + krow * 1280 + ((ch ^ (lane & 7)) << 4));
                    mma16816(co, a[0], a[1], a[2], a[3], b0, b1);
                    if (t == 0) {
                        oscr[256 + (w * 5 + i) * 16 + g] = co[0];
                        oscr[256 + (w * 5 + i) * 16 + 8 + g] = co[2];
                    }
                }
                __syncwarp();
                if (lane < 20) {
                    const float4 v4 = *reinterpret_cast<const float4*>(oscr + 256 + w * 80 + lane * 4);
                    red_add_v4(acc + w * 80 + lane * 4, v4.x, v4.y, v4.z, v4.w);
                }
            }
        }
        TS(5 + s * 6);
        TS2(11);
        if (s < 3) grid_barrier(base + NCTA * (s + 1));
        TS(6 + s * 6);
    }
    __syncthreads();
    if (tid == 0) {
        __threadfence();
        const unsigned old = atomicAdd(&g_ctr, 1u);
        s_flag[1] = (old == base + 4 * NCTA - 1) ? 1u : 0u;
        __threadfence();
    }
    __syncthreads();
    if (s_flag[1]) {
        for (int e = tid; e < D_MODEL; e += NT) {
            float a = 0.f;
#pragma unroll
            for (int i = 0; i < NREP; i++) a += __ldcg(&g_acc[3][i][e]);
            const float o = bf16r(bf16r(a) + __bfloat162float(b2s[e]));
            P.out[e] = __float2bfloat16_rn(__bfloat162float(xs[e]) + o);
        }
    }
    TS(25);
}

}

extern "C" void kernel_launch(void* const* d_in, const int* in_sizes, int n_in,
                              void* d_out, int out_size) {
    Params P;
    P.x = (const bf16*)d_in[0];
    P.kc = (const bf16*)d_in[1];
    P.vc = (const bf16*)d_in[2];
    P.wq = (const bf16*)d_in[3];
    P.wo = (const bf16*)d_in[4];
    P.w1 = (const bf16*)d_in[6];
    P.b1 = (const bf16*)d_in[7];
    P.w2 = (const bf16*)d_in[8];
    P.b2 = (const bf16*)d_in[9];
    P.out = (bf16*)d_out;

    cudaFuncSetAttribute(fused_kernel, cudaFuncAttributeMaxDynamicSharedMemorySize, SMEM_BYTES);

    typedef CUresult (*EncodeFn)(CUtensorMap*, CUtensorMapDataType, cuuint32_t, void*, const cuuint64_t*, const cuuint64_t*,
                                 const cuuint32_t*, const cuuint32_t*, CUtensorMapInterleave, CUtensorMapSwizzle,
                                 CUtensorMapL2promotion, CUtensorMapFloatOOBfill);
    void* fn = nullptr;
    cudaDriverEntryPointQueryResult qres;
    cudaGetDriverEntryPoint("cuTensorMapEncodeTiled", &fn, cudaEnableDefault, &qres);
    EncodeFn encode = (EncodeFn)fn;
    CUtensorMap tm_wq, tm_wo;
    {
        cuuint64_t dims[2] = {(cuuint64_t)(NHEAD * DH), (cuuint64_t)D_MODEL};
        cuuint64_t strides[1] = {(cuuint64_t)(NHEAD * DH * 2)};
        cuuint32_t box[2] = {64, 128};
        cuuint32_t es[2] = {1, 1};
        encode(&tm_wq, CU_TENSOR_MAP_DATA_TYPE_BFLOAT16, 2, (void*)P.wq, dims, strides, box, es, CU_TENSOR_MAP_INTERLEAVE_NONE,
               CU_TENSOR_MAP_SWIZZLE_128B, CU_TENSOR_MAP_L2_PROMOTION_NONE, CU_TENSOR_MAP_FLOAT_OOB_FILL_NONE);
    }
    {
        cuuint64_t dims[2] = {(cuuint64_t)D_MODEL, (cuuint64_t)(NHEAD * DH)};
        cuuint64_t strides[1] = {(cuuint64_t)(D_MODEL * 2)};
        cuuint32_t box[2] = {64, 64};
        cuuint32_t es[2] = {1, 1};
        encode(&tm_wo, CU_TENSOR_MAP_DATA_TYPE_BFLOAT16, 2, (void*)P.wo, dims, strides, box, es, CU_TENSOR_MAP_INTERLEAVE_NONE,
               CU_TENSOR_MAP_SWIZZLE_128B, CU_TENSOR_MAP_L2_PROMOTION_NONE, CU_TENSOR_MAP_FLOAT_OOB_FILL_NONE);
    }

    cudaLaunchConfig_t cfg = {};
    cfg.gridDim = dim3(NCTA);
    cfg.blockDim = dim3(NT);
    cfg.dynamicSmemBytes = SMEM_BYTES;
    cfg.stream = cudaStreamPerThread;
    cudaLaunchAttribute at[2];
    at[0].id = cudaLaunchAttributeClusterDimension;
    at[0].val.clusterDim.x = 2; at[0].val.clusterDim.y = 1; at[0].val.clusterDim.z = 1;
    at[1].id = cudaLaunchAttributeCooperative;
    at[1].val.cooperative = 1;
    cfg.attrs = at;
    cfg.numAttrs = 1;
    cudaLaunchKernelEx(&cfg, fused_kernel, P, tm_wq, tm_wo);
}
```

```cpp
#include <cuda_runtime.h>
#include <cuda.h>
#include <cuda_bf16.h>
#include <stdint.h>

typedef __nv_bfloat16 bf16;

namespace {

constexpr int D_MODEL = 640;
constexpr int NHEAD = 32;
constexpr int SEQ = 4096;
constexpr int DH = 128;
constexpr int FF = 1728;
constexpr int NCTA = 128;
constexpr int NT = 256;
constexpr int KREG_TILES = 5;
constexpr int KSM_TILES = 3;
constexpr int MLP_UNITS = 16;
constexpr int MLP_CTAS = FF / MLP_UNITS;

constexpr int OFF_STAGE = 0;
constexpr int OFF_W2 = 81920;
constexpr int OFF_W1 = OFF_W2 + 20480;
constexpr int OFF_K = OFF_W1 + 20480;
constexpr int OFF_XS = OFF_K + 98304;
constexpr int OFF_XN = OFF_XS + 1280;
constexpr int OFF_O = OFF_XN + 1280;
constexpr int OFF_P = OFF_O + 4096;
constexpr int OFF_Q = OFF_P + 2048;
constexpr int OFF_OEX = OFF_Q + 256;
constexpr int OFF_STAT = OFF_OEX + 512;
constexpr int OFF_RED = OFF_STAT + 80;
constexpr int OFF_HS = OFF_RED + 96;
constexpr int OFF_B2 = OFF_HS + 320;
constexpr int OFF_XBAR = OFF_B2 + 1280;
constexpr int SMEM_BYTES = OFF_XBAR + 16;

static_assert(SMEM_BYTES <= 232448, "smem");
constexpr int NREP = 8;
constexpr int VL = 2;
constexpr int NVB = 2;
constexpr unsigned SPIN_LIMIT = 1u << 24;

__device__ unsigned int g_ctr;
__device__ float g_acc[4][NREP][D_MODEL];
__device__ uint4 g_ml[2][NCTA];

struct Params {
    const bf16* x; const bf16* kc; const bf16* vc; const bf16* wq; const bf16* wo;
    const bf16* w1; const bf16* b1; const bf16* w2; const bf16* b2; bf16* out;
};

__device__ __forceinline__ float bf16r(float x) { return __bfloat162float(__float2bfloat16_rn(x)); }
__device__ __forceinline__ float bflo(uint32_t u) { return __uint_as_float(u << 16); }
__device__ __forceinline__ float bfhi(uint32_t u) { return __uint_as_float(u & 0xffff0000u); }

__device__ __forceinline__ uint32_t smem_u32(const void* p) { return (uint32_t)__cvta_generic_to_shared(p); }

__device__ __forceinline__ void mbar_init(uint32_t bar, uint32_t cnt) {
    asm volatile("mbarrier.init.shared::cta.b64 [%0], %1;" :: "r"(bar), "r"(cnt) : "memory");
}
__device__ __forceinline__ void mbar_expect_tx(uint32_t bar, uint32_t bytes) {
    asm volatile("mbarrier.arrive.expect_tx.shared::cta.b64 _, [%0], %1;" :: "r"(bar), "r"(bytes) : "memory");
}
__device__ __forceinline__ void mbar_wait(uint32_t bar, uint32_t parity) {
    unsigned it = 0;
    while (true) {
        uint32_t ok;
        asm volatile("{\n\t.reg .pred p;\n\tmbarrier.try_wait.parity.shared::cta.b64 p, [%1], %2;\n\tselp.u32 %0, 1, 0, p;\n\t}"
                     : "=r"(ok) : "r"(bar), "r"(parity) : "memory");
        if (ok) break;
        if (++it > SPIN_LIMIT) __trap();
    }
}
__device__ __forceinline__ void tma_2d_hint(uint32_t dst, const CUtensorMap* tm, int c0, int c1, uint32_t bar, uint64_t pol) {
    asm volatile("cp.async.bulk.tensor.2d.shared::cluster.global.mbarrier::complete_tx::bytes.L2::cache_hint [%0], [%1, {%3, %4}], [%2], %5;"
                 :: "r"(dst), "l"(tm), "r"(bar), "r"(c0), "r"(c1), "l"(pol) : "memory");
}
__device__ __forceinline__ void bulk_prefetch_l2(const void* src, uint32_t bytes) {
    asm volatile("cp.async.bulk.prefetch.L2.global [%0], %1;" :: "l"(src), "r"(bytes) : "memory");
}
__device__ __forceinline__ float ex2(float x) { float y; asm("ex2.approx.ftz.f32 %0, %1;" : "=f"(y) : "f"(x)); return y; }
__device__ __forceinline__ void cp_async16_hint(uint32_t dst, const void* src, uint64_t pol) {
    asm volatile("cp.async.cg.shared.global.L2::cache_hint [%0], [%1], 16, %2;" :: "r"(dst), "l"(src), "l"(pol) : "memory");
}
__device__ __forceinline__ void cp_async_wait_all() { asm volatile("cp.async.wait_all;" ::: "memory"); }
__device__ __forceinline__ void cp_async_commit() { asm volatile("cp.async.commit_group;" ::: "memory"); }
template <int N> __device__ __forceinline__ void cp_async_wait_group() { asm volatile("cp.async.wait_group %0;" :: "n"(N) : "memory"); }

__device__ __forceinline__ void ldg128_hint(uint32_t (&r)[4], const void* p, uint64_t pol) {
    asm volatile("ld.global.nc.L1::no_allocate.L2::cache_hint.v4.u32 {%0,%1,%2,%3}, [%4], %5;"
                 : "=r"(r[0]), "=r"(r[1]), "=r"(r[2]), "=r"(r[3]) : "l"(p), "l"(pol));
}
__device__ __forceinline__ void mma16816(float (&c)[4], uint32_t a0, uint32_t a1, uint32_t a2, uint32_t a3,
                                         uint32_t b0, uint32_t b1) {
    asm volatile("mma.sync.aligned.m16n8k16.row.col.f32.bf16.bf16.f32 {%0,%1,%2,%3}, {%4,%5,%6,%7}, {%8,%9}, {%0,%1,%2,%3};"
                 : "+f"(c[0]), "+f"(c[1]), "+f"(c[2]), "+f"(c[3])
                 : "r"(a0), "r"(a1), "r"(a2), "r"(a3), "r"(b0), "r"(b1));
}
__device__ __forceinline__ void ldmatrix4(uint32_t (&r)[4], uint32_t addr) {
    asm volatile("ldmatrix.sync.aligned.m8n8.x4.shared.b16 {%0,%1,%2,%3}, [%4];"
                 : "=r"(r[0]), "=r"(r[1]), "=r"(r[2]), "=r"(r[3]) : "r"(addr) : "memory");
}
__device__ __forceinline__ void red_add_v4(float* p, float a, float b, float c, float d) {
    asm volatile("red.global.add.v4.f32 [%0], {%1,%2,%3,%4};" :: "l"(p), "f"(a), "f"(b), "f"(c), "f"(d) : "memory");
}
__device__ __forceinline__ unsigned ld_acquire(const unsigned* p) {
    unsigned v; asm volatile("ld.acquire.gpu.global.u32 %0, [%1];" : "=r"(v) : "l"(p) : "memory"); return v;
}
__device__ __forceinline__ uint32_t mapa(uint32_t addr, uint32_t rank) {
    uint32_t r; asm volatile("mapa.shared::cluster.u32 %0, %1, %2;" : "=r"(r) : "r"(addr), "r"(rank)); return r;
}
__device__ __forceinline__ void st_async_b32(uint32_t addr, uint32_t v, uint32_t bar) {
    asm volatile("st.async.weak.shared::cluster.mbarrier::complete_tx::bytes.b32 [%0], %1, [%2];" :: "r"(addr), "r"(v), "r"(bar) : "memory");
}
__device__ __forceinline__ float warp_sum(float v) {
#pragma unroll
    for (int o = 16; o > 0; o >>= 1) v += __shfl_xor_sync(0xffffffffu, v, o);
    return v;
}

__device__ __forceinline__ void grid_barrier(unsigned target) {
    __syncthreads();
    if (threadIdx.x == 0) {
        __threadfence();
        atomicAdd(&g_ctr, 1u);
        unsigned it = 0;
        while ((int)(ld_acquire(&g_ctr) - target) < 0) { if (++it > SPIN_LIMIT) __trap(); }
    }
    __syncthreads();
}

constexpr float LOG2E = 1.4426950408889634f;

__device__ __forceinline__ void ldmatrix4t(uint32_t (&r)[4], uint32_t addr) {
    asm volatile("ldmatrix.sync.aligned.m8n8.x4.trans.shared.b16 {%0,%1,%2,%3}, [%4];"
                 : "=r"(r[0]), "=r"(r[1]), "=r"(r[2]), "=r"(r[3]) : "r"(addr) : "memory");
}
__device__ __forceinline__ uint32_t pack_bf16(float lo, float hi) {
    uint32_t r; asm("cvt.rn.bf16x2.f32 %0, %1, %2;" : "=r"(r) : "f"(hi), "f"(lo)); return r;
}

__global__ void __launch_bounds__(NT, 1) fused_kernel(const Params P, const __grid_constant__ CUtensorMap tm_wq,
                                                        const __grid_constant__ CUtensorMap tm_wo) {
    extern __shared__ __align__(1024) unsigned char sm[];
    const int tid = threadIdx.x, lane = tid & 31, w = tid >> 5;
    const int g = lane >> 2, t = lane & 3;
    const int b = blockIdx.x, h = b >> 2, c = b & 3, r = b & 1;
    const uint32_t sbase = smem_u32(sm);
    bf16* xs = reinterpret_cast<bf16*>(sm + OFF_XS);
    bf16* xn = reinterpret_cast<bf16*>(sm + OFF_XN);
    bf16* b2s = reinterpret_cast<bf16*>(sm + OFF_B2);
    float* oscr = reinterpret_cast<float*>(sm + OFF_O);
    bf16* qs = reinterpret_cast<bf16*>(sm + OFF_Q);
    float* oex = reinterpret_cast<float*>(sm + OFF_OEX);
    float* stat = reinterpret_cast<float*>(sm + OFF_STAT);
    float* red = reinterpret_cast<float*>(sm + OFF_RED);
    bf16* hs = reinterpret_cast<bf16*>(sm + OFF_HS);
    volatile unsigned* s_flag = reinterpret_cast<volatile unsigned*>(sm + OFF_STAT + 64);
    const uint32_t bar_stage = sbase + OFF_STAT + 72;
    if (tid < D_MODEL / 8) *reinterpret_cast<uint4*>(xs + tid * 8) = __ldg(reinterpret_cast<const uint4*>(P.x) + tid);
    else if (tid < D_MODEL / 4) *reinterpret_cast<uint4*>(b2s + (tid - 80) * 8) = __ldg(reinterpret_cast<const uint4*>(P.b2) + (tid - 80));
    else if (tid < 162) { if (b < MLP_CTAS) *reinterpret_cast<uint4*>(hs + 16 + (tid - 160) * 8) = __ldg(reinterpret_cast<const uint4*>(P.b1 + b * MLP_UNITS) + (tid - 160)); }
    else if (tid == 192) s_flag[0] = ld_acquire(&g_ctr) >> 9;
    uint64_t pol_first;
    asm volatile("createpolicy.fractional.L2::evict_first.b64 %0, 1.0;" : "=l"(pol_first));
    uint64_t pol_norm;
    asm volatile("createpolicy.fractional.L2::evict_normal.b64 %0, 1.0;" : "=l"(pol_norm));

    const size_t kv_off = (size_t)(h * SEQ + c * 1024 + w * 128) * DH;
    if (tid == 224) {
        mbar_init(bar_stage, 1);
        mbar_init(sbase + OFF_XBAR, 1);
        mbar_init(sbase + OFF_XBAR + 8, 1);
        asm volatile("fence.mbarrier_init.release.cluster;" ::: "memory");
        asm volatile("fence.proxy.async.shared::cta;" ::: "memory");
        mbar_expect_tx(bar_stage, 81920);
#pragma unroll
        for (int i = 0; i < 5; i++) tma_2d_hint(sbase + OFF_STAGE + i * 16384, &tm_wq, h * DH + r * 64, i * 128, bar_stage, pol_first);
    }
    const uint32_t kb = sbase + OFF_K + w * (KSM_TILES * 16 * 256);
    {
        const bf16* kq = P.kc + kv_off + KREG_TILES * 16 * DH;
#pragma unroll 1
        for (int it = 0; it < KSM_TILES * 8; it++) {
            const int idx = it * 32 + lane;
            const int row = idx >> 4, ch = idx & 15;
            cp_async16_hint(kb + row * 256 + ((ch ^ (row & 7)) << 4), kq + row * DH + ch * 8, pol_first);
        }
    }
    cp_async_commit();
    if (b < MLP_CTAS) {
#pragma unroll 1
        for (int idx = tid; idx < 2 * D_MODEL; idx += NT) {
            const int row = idx >> 1, hf = idx & 1;
            cp_async16_hint(sbase + OFF_W1 + row * 32 + hf * 16, P.w1 + (size_t)row * FF + b * MLP_UNITS + hf * 8, pol_first);
            const int r2 = idx / 80, ch = idx - r2 * 80;
            cp_async16_hint(sbase + OFF_W2 + r2 * 1280 + ((ch ^ (r2 & 7)) << 4), P.w2 + (size_t)(b * MLP_UNITS) * D_MODEL + idx * 8, pol_first);
        }
    }
    cp_async_commit();
    if (b == 1) for (int e = tid; e < 3 * NREP * D_MODEL; e += NT) (&g_acc[1][0][0])[e] = 0.f;
    uint32_t kreg[KREG_TILES][2][4][4];
    __syncthreads();
    asm volatile("barrier.cluster.arrive.relaxed.aligned;" ::: "memory");
    const unsigned epoch = s_flag[0];
    const unsigned base = epoch << 9;

#pragma unroll 1
    for (int s = 0; s < 4; s++) {
        {
            float v[4] = {0.f, 0.f, 0.f, 0.f};
            if (tid < D_MODEL / 4) {
                const uint2 xr = *reinterpret_cast<const uint2*>(xs + tid * 4);
                v[0] = bflo(xr.x); v[1] = bfhi(xr.x); v[2] = bflo(xr.y); v[3] = bfhi(xr.y);
                if (s != 0) {
                    float4 a = __ldcg(reinterpret_cast<const float4*>(&g_acc[s - 1][0][0]) + tid);
#pragma unroll
                    for (int i = 1; i < NREP; i++) {
                        const float4 a2 = __ldcg(reinterpret_cast<const float4*>(&g_acc[s - 1][i][0]) + tid);
                        a.x += a2.x; a.y += a2.y; a.z += a2.z; a.w += a2.w;
                    }
                    a.x = bf16r(a.x); a.y = bf16r(a.y); a.z = bf16r(a.z); a.w = bf16r(a.w);
                    if (s == 2) {
                        const uint2 br = *reinterpret_cast<const uint2*>(b2s + tid * 4);
                        a.x = bf16r(a.x + bflo(br.x)); a.y = bf16r(a.y + bfhi(br.x));
                        a.z = bf16r(a.z + bflo(br.y)); a.w = bf16r(a.w + bfhi(br.y));
                    }
                    v[0] = bf16r(v[0] + a.x); v[1] = bf16r(v[1] + a.y); v[2] = bf16r(v[2] + a.z); v[3] = bf16r(v[3] + a.w);
                    *reinterpret_cast<uint2*>(xs + tid * 4) = make_uint2(pack_bf16(v[0], v[1]), pack_bf16(v[2], v[3]));
                }
            }
            if (s == 2 && b == 0) {
                for (int e = tid; e < NREP * D_MODEL; e += NT) (&g_acc[0][0][0])[e] = 0.f;
            }
#pragma unroll 1
            for (int rep = 0; rep <= (s & 1); rep++) {
                float mean = 0.25f * ((v[0] + v[1]) + (v[2] + v[3]));
                float m2 = (v[0] - mean) * (v[0] - mean) + (v[1] - mean) * (v[1] - mean) +
                           (v[2] - mean) * (v[2] - mean) + (v[3] - mean) * (v[3] - mean);
                float hn = 2.f;
#pragma unroll
                for (int o = 1; o < 32; o <<= 1) {
                    const float mo = __shfl_xor_sync(0xffffffffu, mean, o);
                    const float qo = __shfl_xor_sync(0xffffffffu, m2, o);
                    const float d = mo - mean;
                    m2 = m2 + qo + d * d * hn;
                    mean = 0.5f * (mean + mo);
                    hn *= 2.f;
                }
                float* rd = red + rep * 12;
                if (lane == 0 && w < 5) { rd[2 * w] = mean; rd[2 * w + 1] = m2; }
                __syncthreads();
                float gm = 0.f, gq = 0.f;
#pragma unroll
                for (int i = 0; i < 5; i++) { gm += rd[2 * i]; gq += rd[2 * i + 1]; }
                gm *= 0.2f;
#pragma unroll
                for (int i = 0; i < 5; i++) { const float d = rd[2 * i] - gm; gq += 128.f * d * d; }
                const float mb = bf16r(gm);
                const float den = bf16r(sqrtf(bf16r(bf16r(gq * (1.0f / D_MODEL)) + 1e-5f)));
#pragma unroll
                for (int i = 0; i < 4; i++) v[i] = bf16r(__fdividef(bf16r(v[i] - mb), den));
            }
            if (tid < D_MODEL / 4)
                *reinterpret_cast<uint2*>(xn + tid * 4) = make_uint2(pack_bf16(v[0], v[1]), pack_bf16(v[2], v[3]));
        }
        if (s == 1) cp_async_wait_all();
        __syncthreads();
        float* acc = &g_acc[s][b & (NREP - 1)][0];

        if (!(s & 1)) {
            const int pass = s >> 1;
            mbar_wait(bar_stage, 0);
            {
                float cq[4][4];
#pragma unroll
                for (int i = 0; i < 4; i++) { cq[i][0] = cq[i][1] = cq[i][2] = cq[i][3] = 0.f; }
#pragma unroll
                for (int k5 = 0; k5 < 5; k5++) {
                    const int ks = w * 5 + k5;
                    const uint32_t b0 = *reinterpret_cast<const uint32_t*>(xn + ks * 16 + 2 * t);
                    const uint32_t b1 = *reinterpret_cast<const uint32_t*>(xn + ks * 16 + 2 * t + 8);
                    const int krow = ks * 16 + (lane & 7) + ((lane >> 4) & 1) * 8;
#pragma unroll
                    for (int mt = 0; mt < 4; mt++) {
                        uint32_t a[4];
                        ldmatrix4t(a, sbase + OFF_STAGE + krow * 128 + (((2 * mt + ((lane >> 3) & 1)) ^ (lane & 7)) << 4));
                        mma16816(cq[mt], a[0], a[1], a[2], a[3], b0, b1);
                    }
                }
                if (t == 0) {
#pragma unroll
                    for (int mt = 0; mt < 4; mt++) { oscr[w * 64 + mt * 16 + g] = cq[mt][0]; oscr[w * 64 + mt * 16 + 8 + g] = cq[mt][2]; }
                }
            }
            __syncthreads();
            if (s == 0) asm volatile("barrier.cluster.wait.aligned;" ::: "memory");
            if (tid < 32) {
                float s0 = 0.f, s1 = 0.f;
#pragma unroll
                for (int i = 0; i < 8; i++) { const float2 v2 = *reinterpret_cast<const float2*>(oscr + i * 64 + 2 * tid); s0 += v2.x; s1 += v2.y; }
                const uint32_t qp = pack_bf16(s0, s1);
                *reinterpret_cast<uint32_t*>(qs + r * 64 + 2 * tid) = qp;
                st_async_b32(mapa(sbase + OFF_Q + (r * 64 + 2 * tid) * 2, r ^ 1), qp, mapa(sbase + OFF_XBAR, r ^ 1));
                if (tid == 0) { mbar_expect_tx(sbase + OFF_XBAR, 128); mbar_expect_tx(sbase + OFF_XBAR + 8, 256); }
            }
            const uint32_t vland = sbase + OFF_STAGE + w * (VL * 4096);
#pragma unroll 1
            for (int it = 0; it < VL * 8; it++) {
                const int idx = it * 32 + lane;
                const int row = idx >> 4, ch = idx & 15;
                cp_async16_hint(vland + row * 256 + ((ch ^ (row & 7)) << 4), P.vc + kv_off + row * DH + ch * 8, pol_first);
            }
            cp_async_commit();
            if (s == 0) {
                const bf16* kp = P.kc + kv_off + (g * DH + t * 8);
#pragma unroll
                for (int i = 0; i < KREG_TILES; i++)
#pragma unroll
                    for (int hh = 0; hh < 2; hh++)
#pragma unroll
                        for (int j = 0; j < 4; j++)
                            ldg128_hint(kreg[i][hh][j], kp + (i * 16 + hh * 8) * DH + j * 32, pol_first);
            }
            __syncthreads();
            mbar_wait(sbase + OFF_XBAR, pass);

            float sc[8][2];
            {
                float cacc[KREG_TILES][4];
#pragma unroll
                for (int i = 0; i < KREG_TILES; i++) { cacc[i][0] = cacc[i][1] = cacc[i][2] = cacc[i][3] = 0.f; }
#pragma unroll
                for (int j = 0; j < 4; j++) {
                    const uint4 qv = *reinterpret_cast<const uint4*>(qs + j * 32 + t * 8);
#pragma unroll
                    for (int i = 0; i < KREG_TILES; i++) {
                        mma16816(cacc[i], kreg[i][0][j][0], kreg[i][1][j][0], kreg[i][0][j][1], kreg[i][1][j][1], qv.x, qv.y);
                        mma16816(cacc[i], kreg[i][0][j][2], kreg[i][1][j][2], kreg[i][0][j][3], kreg[i][1][j][3], qv.z, qv.w);
                    }
                }
#pragma unroll
                for (int i = 0; i < KREG_TILES; i++) { sc[i][0] = cacc[i][0]; sc[i][1] = cacc[i][2]; }
            }
            {
                if (s == 0) {
                    if (lane == 0) bulk_prefetch_l2(P.vc + kv_off + VL * 16 * DH, (8 - VL) * 4096);
                    cp_async_wait_group<2>();
                    __syncwarp();
                }
                float cacc[KSM_TILES][4];
#pragma unroll
                for (int tt = 0; tt < KSM_TILES; tt++) { cacc[tt][0] = cacc[tt][1] = cacc[tt][2] = cacc[tt][3] = 0.f; }
                const int row0 = (lane & 7) + ((lane >> 3) & 1) * 8;
#pragma unroll 4
                for (int ks = 0; ks < 8; ks++) {
                    const uint32_t b0 = *reinterpret_cast<const uint32_t*>(qs + ks * 16 + 2 * t);
                    const uint32_t b1 = *reinterpret_cast<const uint32_t*>(qs + ks * 16 + 2 * t + 8);
                    const int ch = 2 * ks + (lane >> 4);
                    const uint32_t ad = kb + row0 * 256 + ((ch ^ (lane & 7)) << 4);
#pragma unroll
                    for (int tt = 0; tt < KSM_TILES; tt++) {
                        uint32_t a[4];
                        ldmatrix4(a, ad + tt * 4096);
                        mma16816(cacc[tt], a[0], a[1], a[2], a[3], b0, b1);
                    }
                }
#pragma unroll
                for (int tt = 0; tt < KSM_TILES; tt++) { sc[KREG_TILES + tt][0] = cacc[tt][0]; sc[KREG_TILES + tt][1] = cacc[tt][2]; }
            }
            bf16* pw = reinterpret_cast<bf16*>(sm + OFF_P + w * 256);
            {
                float s4[4];
#pragma unroll
                for (int q2 = 0; q2 < 4; q2++) {
                    const int i = q2 >> 1, k2 = q2 & 1;
                    const float v01 = (t & 1) ? sc[2 + i][k2] : sc[i][k2];
                    const float v23 = (t & 1) ? sc[6 + i][k2] : sc[4 + i][k2];
                    s4[q2] = (t & 2) ? v23 : v01;
                }
                float mx = -INFINITY;
#pragma unroll
                for (int q2 = 0; q2 < 4; q2++) {
                    s4[q2] = bf16r(bf16r(s4[q2]) * 0.08838834764831845f);
                    mx = fmaxf(mx, s4[q2]);
                }
#pragma unroll
                for (int o = 1; o < 32; o <<= 1) mx = fmaxf(mx, __shfl_xor_sync(0xffffffffu, mx, o));
                float l = 0.f;
#pragma unroll
                for (int q2 = 0; q2 < 4; q2++) {
                    const bf16 pb = __float2bfloat16_rn(ex2((s4[q2] - mx) * LOG2E));
                    l += __bfloat162float(pb);
                    pw[(2 * t + (q2 >> 1)) * 16 + (q2 & 1) * 8 + g] = pb;
                }
                l = warp_sum(l);
                if (lane == 0) { stat[2 * w] = mx; stat[2 * w + 1] = l; }
            }
            __syncthreads();
            float m_cta = stat[0];
#pragma unroll
            for (int i = 1; i < 8; i++) m_cta = fmaxf(m_cta, stat[2 * i]);
            const float wfac = ex2((stat[2 * w] - m_cta) * LOG2E);
            if (tid == 0) {
                float l_cta = 0.f;
#pragma unroll
                for (int i = 0; i < 8; i++) l_cta += stat[2 * i + 1] * ex2((stat[2 * i] - m_cta) * LOG2E);
                asm volatile("st.relaxed.gpu.global.v4.u32 [%0], {%1,%2,%3,%4};" :: "l"(&g_ml[pass][b]),
                             "r"(__float_as_uint(m_cta)), "r"(__float_as_uint(l_cta)), "r"(epoch * 2 + pass + 1), "r"(0u) : "memory");
            }

            {
                const bf16* vbase = P.vc + kv_off + (4 * t) * DH + g * 8;
                float* ow = oscr + w * 128;
                constexpr int NK = 8 - VL;
                static_assert(NK % NVB == 0, "NVB");
                uint32_t vbuf[NVB][4][4];
#pragma unroll
                for (int u = 0; u < NVB - 1; u++)
#pragma unroll
                    for (int i = 0; i < 4; i++) ldg128_hint(vbuf[u][i], vbase + ((VL + u) * 16 + i) * DH, pol_norm);
                cp_async_wait_all();
                __syncwarp();
#pragma unroll 4
                for (int mt = 0; mt < 8; mt++) {
                    float cl[4] = {0.f, 0.f, 0.f, 0.f};
#pragma unroll
                    for (int kt = 0; kt < VL; kt++) {
                        const uint32_t b0 = *reinterpret_cast<const uint32_t*>(pw + kt * 16 + 2 * t);
                        const uint32_t b1 = *reinterpret_cast<const uint32_t*>(pw + kt * 16 + 2 * t + 8);
                        const int row = kt * 16 + (lane & 7) + ((lane >> 4) & 1) * 8;
                        uint32_t a[4];
                        ldmatrix4t(a, vland + row * 256 + (((2 * mt + ((lane >> 3) & 1)) ^ (lane & 7)) << 4));
                        mma16816(cl, a[0], a[1], a[2], a[3], b0, b1);
                    }
                    if (t == 0) { ow[mt * 16 + g] = cl[0] * wfac; ow[mt * 16 + 8 + g] = cl[2] * wfac; }
                }
                __syncwarp();
                if (w != 7) asm volatile("bar.arrive 1, 256;" ::: "memory");
                float oacc[4][4];
#pragma unroll
                for (int i = 0; i < 4; i++) { oacc[i][0] = oacc[i][1] = oacc[i][2] = oacc[i][3] = 0.f; }
#pragma unroll 1
                for (int hf = 0; hf < 2; hf++) {
#pragma unroll 1
                    for (int k0 = 0; k0 < NK; k0 += NVB) {
                        if (w == 7 && hf == 1 && k0 == 2) {
                            asm volatile("bar.sync 1, 256;" ::: "memory");
                            if (lane == 0) {
                                mbar_expect_tx(bar_stage, 81920);
#pragma unroll 1
                                for (int i = 0; i < 10; i++) tma_2d_hint(sbase + OFF_STAGE + i * 8192, &tm_wo, i * 64, h * DH + r * 64, bar_stage, pol_first);
                            }
                            __syncwarp();
                        }
#pragma unroll
                        for (int u = 0; u < NVB; u++) {
                            const int kt = k0 + u;
                            int nk = kt + NVB - 1, nh = hf;
                            if (nk >= NK) { nk -= NK; nh = hf + 1; }
                            if (nh < 2) {
                                const bf16* vp = vbase + (VL + nk) * 16 * DH + nh * 64;
#pragma unroll
                                for (int i = 0; i < 4; i++) ldg128_hint(vbuf[(u + NVB - 1) % NVB][i], vp + i * DH, pol_norm);
                            }
                            const uint2 pb = *reinterpret_cast<const uint2*>(pw + (VL + kt) * 16 + 4 * t);
#pragma unroll
                            for (int e = 0; e < 4; e++)
                                mma16816(oacc[e], __byte_perm(vbuf[u][0][e], vbuf[u][1][e], 0x5410), __byte_perm(vbuf[u][0][e], vbuf[u][1][e], 0x7632),
                                         __byte_perm(vbuf[u][2][e], vbuf[u][3][e], 0x5410), __byte_perm(vbuf[u][2][e], vbuf[u][3][e], 0x7632), pb.x, pb.y);
                        }
                    }
                    if (t == 0) {
                        float* o2 = ow + hf * 64 + g * 8;
                        float4 u0 = *reinterpret_cast<float4*>(o2), u1 = *reinterpret_cast<float4*>(o2 + 4);
                        u0.x += oacc[0][0] * wfac; u0.y += oacc[0][2] * wfac; u0.z += oacc[1][0] * wfac; u0.w += oacc[1][2] * wfac;
                        u1.x += oacc[2][0] * wfac; u1.y += oacc[2][2] * wfac; u1.z += oacc[3][0] * wfac; u1.w += oacc[3][2] * wfac;
                        *reinterpret_cast<float4*>(o2) = u0;
                        *reinterpret_cast<float4*>(o2 + 4) = u1;
                    }
#pragma unroll
                    for (int i = 0; i < 4; i++) { oacc[i][0] = oacc[i][1] = oacc[i][2] = oacc[i][3] = 0.f; }
                }
            }
            __syncthreads();
            if (tid < 128) {
                uint4 rec[4];
                {
                    unsigned it = 0;
                    const unsigned tag = epoch * 2 + pass + 1;
                    while (true) {
#pragma unroll
                        for (int i = 0; i < 4; i++)
                            asm volatile("ld.relaxed.gpu.global.v4.u32 {%0,%1,%2,%3}, [%4];"
                                         : "=r"(rec[i].x), "=r"(rec[i].y), "=r"(rec[i].z), "=r"(rec[i].w)
                                         : "l"(&g_ml[pass][(b & ~3) + i]) : "memory");
                        if (rec[0].z == tag && rec[1].z == tag && rec[2].z == tag && rec[3].z == tag) break;
                        if (++it > SPIN_LIMIT) __trap();
                    }
                }
                const float M = fmaxf(fmaxf(__uint_as_float(rec[0].x), __uint_as_float(rec[1].x)),
                                      fmaxf(__uint_as_float(rec[2].x), __uint_as_float(rec[3].x)));
                float L = 0.f;
#pragma unroll
                for (int i = 0; i < 4; i++) L += __uint_as_float(rec[i].y) * ex2((__uint_as_float(rec[i].x) - M) * LOG2E);
                const float scale = __fdividef(ex2((m_cta - M) * LOG2E), L);
                float sum = 0.f;
#pragma unroll
                for (int i = 0; i < 8; i++) sum += oscr[i * 128 + tid];
                if ((tid >> 6) == r) oex[r * 64 + (tid & 63)] = sum * scale;
                else st_async_b32(mapa(sbase + OFF_OEX + (r * 64 + (tid & 63)) * 4, r ^ 1), __float_as_uint(sum * scale), mapa(sbase + OFF_XBAR + 8, r ^ 1));
            }
            __syncthreads();
            if (tid < 64) {
                mbar_wait(sbase + OFF_XBAR + 8, pass);
                const float o = oex[tid] + oex[64 + tid];
                const bf16 hi = __float2bfloat16_rn(o);
                hs[32 + tid] = hi;
                hs[96 + tid] = __float2bfloat16_rn(o - __bfloat162float(hi));
            }
            mbar_wait(bar_stage, 1);
            __syncthreads();
            {
                float co[5][4];
#pragma unroll
                for (int i = 0; i < 5; i++) { co[i][0] = co[i][1] = co[i][2] = co[i][3] = 0.f; }
#pragma unroll 1
                for (int ks = 0; ks < 4; ks++) {
                    uint32_t b0 = 0, b1 = 0;
                    if (g < 2) {
                        b0 = *reinterpret_cast<const uint32_t*>(hs + 32 + g * 64 + ks * 16 + 2 * t);
                        b1 = *reinterpret_cast<const uint32_t*>(hs + 32 + g * 64 + ks * 16 + 2 * t + 8);
                    }
                    const int krow = ks * 16 + (lane & 7) + ((lane >> 4) & 1) * 8;
#pragma unroll
                    for (int i = 0; i < 5; i++) {
                        const int ch = 2 * (w * 5 + i) + ((lane >> 3) & 1);
                        uint32_t a[4];
                        ldmatrix4t(a, sbase + OFF_STAGE + (ch >> 3) * 8192 + krow * 128 + (((ch ^ lane) & 7) << 4));
                        mma16816(co[i], a[0], a[1], a[2], a[3], b0, b1);
                    }
                }
                if (t == 0) {
#pragma unroll
                    for (int i = 0; i < 5; i++) {
                        oscr[(w * 5 + i) * 16 + g] = co[i][0] + co[i][1];
                        oscr[(w * 5 + i) * 16 + 8 + g] = co[i][2] + co[i][3];
                    }
                }
                __syncwarp();
                if (lane < 20) {
                    const float4 v4 = *reinterpret_cast<const float4*>(oscr + w * 80 + lane * 4);
                    red_add_v4(acc + w * 80 + lane * 4, v4.x, v4.y, v4.z, v4.w);
                }
            }
            if (s == 0) {
                __syncthreads();
                if (tid == 224) {
                    mbar_expect_tx(bar_stage, 81920);
#pragma unroll 1
                    for (int i = 0; i < 5; i++) tma_2d_hint(sbase + OFF_STAGE + i * 16384, &tm_wq, h * DH + r * 64, i * 128, bar_stage, pol_first);
                }
            }
        } else if (b < MLP_CTAS) {
            {
                float ch4[4] = {0.f, 0.f, 0.f, 0.f};
#pragma unroll
                for (int k5 = 0; k5 < 5; k5++) {
                    const int ks = w * 5 + k5;
                    const uint32_t b0 = *reinterpret_cast<const uint32_t*>(xn + ks * 16 + 2 * t);
                    const uint32_t b1 = *reinterpret_cast<const uint32_t*>(xn + ks * 16 + 2 * t + 8);
                    const int krow = ks * 16 + (lane & 7) + ((lane >> 4) & 1) * 8;
                    uint32_t a[4];
                    ldmatrix4t(a, sbase + OFF_W1 + krow * 32 + ((lane >> 3) & 1) * 16);
                    mma16816(ch4, a[0], a[1], a[2], a[3], b0, b1);
                }
                if (t == 0) { oscr[w * 16 + g] = ch4[0]; oscr[w * 16 + 8 + g] = ch4[2]; }
            }
            __syncthreads();
            if (tid < 16) {
                float sum = 0.f;
#pragma unroll
                for (int i = 0; i < 8; i++) sum += oscr[i * 16 + tid];
                const float u = bf16r(bf16r(sum) + __bfloat162float(hs[16 + tid]));
                const float inner = 0.7978845608028654f * (u + 0.044715f * u * u * u);
                const float th = 1.0f - __fdividef(2.0f, ex2(inner * (2.0f * LOG2E)) + 1.0f);
                hs[tid] = __float2bfloat16_rn(0.5f * u * (1.0f + th));
            }
            __syncthreads();
            {
                const uint32_t b0 = *reinterpret_cast<const uint32_t*>(hs + 2 * t);
                const uint32_t b1 = *reinterpret_cast<const uint32_t*>(hs + 2 * t + 8);
                const int krow = (lane & 7) + ((lane >> 4) & 1) * 8;
#pragma unroll
                for (int i = 0; i < 5; i++) {
                    const int ch = 2 * (w * 5 + i) + ((lane >> 3) & 1);
                    uint32_t a[4];
                    float co[4] = {0.f, 0.f, 0.f, 0.f};
                    ldmatrix4t(a, sbase + OFF_W2 + krow * 1280 + ((ch ^ (lane & 7)) << 4));
                    mma16816(co, a[0], a[1], a[2], a[3], b0, b1);
                    if (t == 0) {
                        oscr[256 + (w * 5 + i) * 16 + g] = co[0];
                        oscr[256 + (w * 5 + i) * 16 + 8 + g] = co[2];
                    }
                }
                __syncwarp();
                if (lane < 20) {
                    const float4 v4 = *reinterpret_cast<const float4*>(oscr + 256 + w * 80 + lane * 4);
                    red_add_v4(acc + w * 80 + lane * 4, v4.x, v4.y, v4.z, v4.w);
                }
            }
        }
        if (s < 3) grid_barrier(base + NCTA * (s + 1));
    }
    __syncthreads();
    if (tid == 0) {
        __threadfence();
        const unsigned old = atomicAdd(&g_ctr, 1u);
        s_flag[1] = (old == base + 4 * NCTA - 1) ? 1u : 0u;
        __threadfence();
    }
    __syncthreads();
    if (s_flag[1]) {
        for (int e = tid; e < D_MODEL; e += NT) {
            float a = 0.f;
#pragma unroll
            for (int i = 0; i < NREP; i++) a += __ldcg(&g_acc[3][i][e]);
            const float o = bf16r(bf16r(a) + __bfloat162float(b2s[e]));
            P.out[e] = __float2bfloat16_rn(__bfloat162float(xs[e]) + o);
        }
    }
}

}

extern "C" void kernel_launch(void* const* d_in, const int* in_sizes, int n_in,
                              void* d_out, int out_size) {
    Params P;
    P.x = (const bf16*)d_in[0];
    P.kc = (const bf16*)d_in[1];
    P.vc = (const bf16*)d_in[2];
    P.wq = (const bf16*)d_in[3];
    P.wo = (const bf16*)d_in[4];
    P.w1 = (const bf16*)d_in[6];
    P.b1 = (const bf16*)d_in[7];
    P.w2 = (const bf16*)d_in[8];
    P.b2 = (const bf16*)d_in[9];
    P.out = (bf16*)d_out;

    cudaFuncSetAttribute(fused_kernel, cudaFuncAttributeMaxDynamicSharedMemorySize, SMEM_BYTES);

    typedef CUresult (*EncodeFn)(CUtensorMap*, CUtensorMapDataType, cuuint32_t, void*, const cuuint64_t*, const cuuint64_t*,
                                 const cuuint32_t*, const cuuint32_t*, CUtensorMapInterleave, CUtensorMapSwizzle,
                                 CUtensorMapL2promotion, CUtensorMapFloatOOBfill);
    void* fn = nullptr;
    cudaDriverEntryPointQueryResult qres;
    cudaGetDriverEntryPoint("cuTensorMapEncodeTiled", &fn, cudaEnableDefault, &qres);
    EncodeFn encode = (EncodeFn)fn;
    CUtensorMap tm_wq, tm_wo;
    {
        cuuint64_t dims[2] = {(cuuint64_t)(NHEAD * DH), (cuuint64_t)D_MODEL};
        cuuint64_t strides[1] = {(cuuint64_t)(NHEAD * DH * 2)};
        cuuint32_t box[2] = {64, 128};
        cuuint32_t es[2] = {1, 1};
        encode(&tm_wq, CU_TENSOR_MAP_DATA_TYPE_BFLOAT16, 2, (void*)P.wq, dims, strides, box, es, CU_TENSOR_MAP_INTERLEAVE_NONE,
               CU_TENSOR_MAP_SWIZZLE_128B, CU_TENSOR_MAP_L2_PROMOTION_NONE, CU_TENSOR_MAP_FLOAT_OOB_FILL_NONE);
    }
    {
        cuuint64_t dims[2] = {(cuuint64_t)D_MODEL, (cuuint64_t)(NHEAD * DH)};
        cuuint64_t strides[1] = {(cuuint64_t)(D_MODEL * 2)};
        cuuint32_t box[2] = {64, 64};
        cuuint32_t es[2] = {1, 1};
        encode(&tm_wo, CU_TENSOR_MAP_DATA_TYPE_BFLOAT16, 2, (void*)P.wo, dims, strides, box, es, CU_TENSOR_MAP_INTERLEAVE_NONE,
               CU_TENSOR_MAP_SWIZZLE_128B, CU_TENSOR_MAP_L2_PROMOTION_NONE, CU_TENSOR_MAP_FLOAT_OOB_FILL_NONE);
    }

    cudaLaunchConfig_t cfg = {};
    cfg.gridDim = dim3(NCTA);
    cfg.blockDim = dim3(NT);
    cfg.dynamicSmemBytes = SMEM_BYTES;
    cfg.stream = cudaStreamPerThread;
    cudaLaunchAttribute at[2];
    at[0].id = cudaLaunchAttributeClusterDimension;
    at[0].val.clusterDim.x = 2; at[0].val.clusterDim.y = 1; at[0].val.clusterDim.z = 1;
    at[1].id = cudaLaunchAttributeCooperative;
    at[1].val.cooperative = 1;
    cfg.attrs = at;
    cfg.numAttrs = 2;
    cudaLaunchKernelEx(&cfg, fused_kernel, P, tm_wq, tm_wo);
}
```

```cpp
#include <cuda_runtime.h>
#include <cuda.h>
#include <cuda_bf16.h>
#include <stdint.h>

typedef __nv_bfloat16 bf16;

namespace {

constexpr int D_MODEL = 640;
constexpr int NHEAD = 32;
constexpr int SEQ = 4096;
constexpr int DH = 128;
constexpr int FF = 1728;
constexpr int NCTA = 128;
constexpr int NT = 256;
constexpr int KREG_TILES = 5;
constexpr int KSM_TILES = 3;
constexpr int MLP_UNITS = 16;
constexpr int MLP_CTAS = FF / MLP_UNITS;

constexpr int OFF_STAGE = 0;
constexpr int OFF_W2 = 81920;
constexpr int OFF_W1 = OFF_W2 + 20480;
constexpr int OFF_K = OFF_W1 + 20480;
constexpr int OFF_XS = OFF_K + 98304;
constexpr int OFF_XN = OFF_XS + 1280;
constexpr int OFF_O = OFF_XN + 1280;
constexpr int OFF_P = OFF_O + 4096;
constexpr int OFF_Q = OFF_P + 2048;
constexpr int OFF_OEX = OFF_Q + 256;
constexpr int OFF_STAT = OFF_OEX + 512;
constexpr int OFF_RED = OFF_STAT + 80;
constexpr int OFF_HS = OFF_RED + 96;
constexpr int OFF_B2 = OFF_HS + 320;
constexpr int OFF_XBAR = OFF_B2 + 1280;
constexpr int SMEM_BYTES = OFF_XBAR + 16;

static_assert(SMEM_BYTES <= 232448, "smem");
constexpr int NREP = 8;
constexpr int VL = 2;
constexpr int NVB = 2;
constexpr unsigned SPIN_LIMIT = 1u << 24;

__device__ unsigned int g_ctr;
__device__ float g_acc[4][NREP][D_MODEL];
__device__ uint4 g_ml[2][NCTA];

struct Params {
    const bf16* x; const bf16* kc; const bf16* vc; const bf16* wq; const bf16* wo;
    const bf16* w1; const bf16* b1; const bf16* w2; const bf16* b2; bf16* out;
};

__device__ __forceinline__ float bf16r(float x) { return __bfloat162float(__float2bfloat16_rn(x)); }
__device__ __forceinline__ float bflo(uint32_t u) { return __uint_as_float(u << 16); }
__device__ __forceinline__ float bfhi(uint32_t u) { return __uint_as_float(u & 0xffff0000u); }

__device__ __forceinline__ uint32_t smem_u32(const void* p) { return (uint32_t)__cvta_generic_to_shared(p); }

__device__ __forceinline__ void mbar_init(uint32_t bar, uint32_t cnt) {
    asm volatile("mbarrier.init.shared::cta.b64 [%0], %1;" :: "r"(bar), "r"(cnt) : "memory");
}
__device__ __forceinline__ void mbar_expect_tx(uint32_t bar, uint32_t bytes) {
    asm volatile("mbarrier.arrive.expect_tx.shared::cta.b64 _, [%0], %1;" :: "r"(bar), "r"(bytes) : "memory");
}
__device__ __forceinline__ void mbar_wait(uint32_t bar, uint32_t parity) {
    unsigned it = 0;
    while (true) {
        uint32_t ok;
        asm volatile("{\n\t.reg .pred p;\n\tmbarrier.try_wait.parity.shared::cta.b64 p, [%1], %2;\n\tselp.u32 %0, 1, 0, p;\n\t}"
                     : "=r"(ok) : "r"(bar), "r"(parity) : "memory");
        if (ok) break;
        if (++it > SPIN_LIMIT) __trap();
    }
}
__device__ __forceinline__ void tma_2d_hint(uint32_t dst, const CUtensorMap* tm, int c0, int c1, uint32_t bar, uint64_t pol) {
    asm volatile("cp.async.bulk.tensor.2d.shared::cluster.global.mbarrier::complete_tx::bytes.L2::cache_hint [%0], [%1, {%3, %4}], [%2], %5;"
                 :: "r"(dst), "l"(tm), "r"(bar), "r"(c0), "r"(c1), "l"(pol) : "memory");
}
__device__ __forceinline__ void bulk_prefetch_l2(const void* src, uint32_t bytes) {
    asm volatile("cp.async.bulk.prefetch.L2.global [%0], %1;" :: "l"(src), "r"(bytes) : "memory");
}
__device__ __forceinline__ float ex2(float x) { float y; asm("ex2.approx.ftz.f32 %0, %1;" : "=f"(y) : "f"(x)); return y; }
__device__ __forceinline__ void cp_async16_hint(uint32_t dst, const void* src, uint64_t pol) {
    asm volatile("cp.async.cg.shared.global.L2::cache_hint [%0], [%1], 16, %2;" :: "r"(dst), "l"(src), "l"(pol) : "memory");
}
__device__ __forceinline__ void cp_async_wait_all() { asm volatile("cp.async.wait_all;" ::: "memory"); }
__device__ __forceinline__ void cp_async_commit() { asm volatile("cp.async.commit_group;" ::: "memory"); }
template <int N> __device__ __forceinline__ void cp_async_wait_group() { asm volatile("cp.async.wait_group %0;" :: "n"(N) : "memory"); }

__device__ __forceinline__ void ldg128_hint(uint32_t (&r)[4], const void* p, uint64_t pol) {
    asm volatile("ld.global.nc.L1::no_allocate.L2::cache_hint.v4.u32 {%0,%1,%2,%3}, [%4], %5;"
                 : "=r"(r[0]), "=r"(r[1]), "=r"(r[2]), "=r"(r[3]) : "l"(p), "l"(pol));
}
__device__ __forceinline__ void mma16816(float (&c)[4], uint32_t a0, uint32_t a1, uint32_t a2, uint32_t a3,
                                         uint32_t b0, uint32_t b1) {
    asm volatile("mma.sync.aligned.m16n8k16.row.col.f32.bf16.bf16.f32 {%0,%1,%2,%3}, {%4,%5,%6,%7}, {%8,%9}, {%0,%1,%2,%3};"
                 : "+f"(c[0]), "+f"(c[1]), "+f"(c[2]), "+f"(c[3])
                 : "r"(a0), "r"(a1), "r"(a2), "r"(a3), "r"(b0), "r"(b1));
}
__device__ __forceinline__ void ldmatrix4(uint32_t (&r)[4], uint32_t addr) {
    asm volatile("ldmatrix.sync.aligned.m8n8.x4.shared.b16 {%0,%1,%2,%3}, [%4];"
                 : "=r"(r[0]), "=r"(r[1]), "=r"(r[2]), "=r"(r[3]) : "r"(addr) : "memory");
}
__device__ __forceinline__ void red_add_v4(float* p, float a, float b, float c, float d) {
    asm volatile("red.global.add.v4.f32 [%0], {%1,%2,%3,%4};" :: "l"(p), "f"(a), "f"(b), "f"(c), "f"(d) : "memory");
}
__device__ __forceinline__ unsigned ld_acquire(const unsigned* p) {
    unsigned v; asm volatile("ld.acquire.gpu.global.u32 %0, [%1];" : "=r"(v) : "l"(p) : "memory"); return v;
}
__device__ __forceinline__ uint32_t mapa(uint32_t addr, uint32_t rank) {
    uint32_t r; asm volatile("mapa.shared::cluster.u32 %0, %1, %2;" : "=r"(r) : "r"(addr), "r"(rank)); return r;
}
__device__ __forceinline__ void st_async_b32(uint32_t addr, uint32_t v, uint32_t bar) {
    asm volatile("st.async.weak.shared::cluster.mbarrier::complete_tx::bytes.b32 [%0], %1, [%2];" :: "r"(addr), "r"(v), "r"(bar) : "memory");
}
__device__ __forceinline__ float warp_sum(float v) {
#pragma unroll
    for (int o = 16; o > 0; o >>= 1) v += __shfl_xor_sync(0xffffffffu, v, o);
    return v;
}

__device__ __forceinline__ void grid_barrier(unsigned target) {
    __syncthreads();
    if (threadIdx.x == 0) {
        __threadfence();
        atomicAdd(&g_ctr, 1u);
        unsigned it = 0;
        while ((int)(ld_acquire(&g_ctr) - target) < 0) { if (++it > SPIN_LIMIT) __trap(); }
    }
    __syncthreads();
}

constexpr float LOG2E = 1.4426950408889634f;

__device__ __forceinline__ void ldmatrix4t(uint32_t (&r)[4], uint32_t addr) {
    asm volatile("ldmatrix.sync.aligned.m8n8.x4.trans.shared.b16 {%0,%1,%2,%3}, [%4];"
                 : "=r"(r[0]), "=r"(r[1]), "=r"(r[2]), "=r"(r[3]) : "r"(addr) : "memory");
}
__device__ __forceinline__ uint32_t pack_bf16(float lo, float hi) {
    uint32_t r; asm("cvt.rn.bf16x2.f32 %0, %1, %2;" : "=r"(r) : "f"(hi), "f"(lo)); return r;
}

__global__ void __launch_bounds__(NT, 1) fused_kernel(const Params P, const __grid_constant__ CUtensorMap tm_wq,
                                                        const __grid_constant__ CUtensorMap tm_wo) {
    extern __shared__ __align__(1024) unsigned char sm[];
    const int tid = threadIdx.x, lane = tid & 31, w = tid >> 5;
    const int g = lane >> 2, t = lane & 3;
    const int b = blockIdx.x, h = b >> 2, c = b & 3, r = b & 1;
    const uint32_t sbase = smem_u32(sm);
    bf16* xs = reinterpret_cast<bf16*>(sm + OFF_XS);
    bf16* xn = reinterpret_cast<bf16*>(sm + OFF_XN);
    bf16* b2s = reinterpret_cast<bf16*>(sm + OFF_B2);
    float* oscr = reinterpret_cast<float*>(sm + OFF_O);
    bf16* qs = reinterpret_cast<bf16*>(sm + OFF_Q);
    float* oex = reinterpret_cast<float*>(sm + OFF_OEX);
    float* stat = reinterpret_cast<float*>(sm + OFF_STAT);
    float* red = reinterpret_cast<float*>(sm + OFF_RED);
    bf16* hs = reinterpret_cast<bf16*>(sm + OFF_HS);
    volatile unsigned* s_flag = reinterpret_cast<volatile unsigned*>(sm + OFF_STAT + 64);
    const uint32_t bar_stage = sbase + OFF_STAT + 72;
    if (tid < D_MODEL / 8) *reinterpret_cast<uint4*>(xs + tid * 8) = __ldg(reinterpret_cast<const uint4*>(P.x) + tid);
    else if (tid < D_MODEL / 4) *reinterpret_cast<uint4*>(b2s + (tid - 80) * 8) = __ldg(reinterpret_cast<const uint4*>(P.b2) + (tid - 80));
    else if (tid < 162) { if (b < MLP_CTAS) *reinterpret_cast<uint4*>(hs + 16 + (tid - 160) * 8) = __ldg(reinterpret_cast<const uint4*>(P.b1 + b * MLP_UNITS) + (tid - 160)); }
    else if (tid == 192) s_flag[0] = ld_acquire(&g_ctr) >> 9;
    uint64_t pol_first;
    asm volatile("createpolicy.fractional.L2::evict_first.b64 %0, 1.0;" : "=l"(pol_first));
    uint64_t pol_norm;
    asm volatile("createpolicy.fractional.L2::evict_normal.b64 %0, 1.0;" : "=l"(pol_norm));

    const size_t kv_off = (size_t)(h * SEQ + c * 1024 + w * 128) * DH;
    if (tid == 224) {
        mbar_init(bar_stage, 1);
        mbar_init(sbase + OFF_XBAR, 1);
        mbar_init(sbase + OFF_XBAR + 8, 1);
        asm volatile("fence.mbarrier_init.release.cluster;" ::: "memory");
        asm volatile("fence.proxy.async.shared::cta;" ::: "memory");
        mbar_expect_tx(bar_stage, 81920);
#pragma unroll
        for (int i = 0; i < 5; i++) tma_2d_hint(sbase + OFF_STAGE + i * 16384, &tm_wq, h * DH + r * 64, i * 128, bar_stage, pol_first);
    }
    const uint32_t kb = sbase + OFF_K + w * (KSM_TILES * 16 * 256);
    {
        const bf16* kq = P.kc + kv_off + KREG_TILES * 16 * DH;
#pragma unroll 1
        for (int it = 0; it < KSM_TILES * 8; it++) {
            const int idx = it * 32 + lane;
            const int row = idx >> 4, ch = idx & 15;
            cp_async16_hint(kb + row * 256 + ((ch ^ (row & 7)) << 4), kq + row * DH + ch * 8, pol_first);
        }
    }
    cp_async_commit();
    if (b == 1) for (int e = tid; e < 3 * NREP * D_MODEL; e += NT) (&g_acc[1][0][0])[e] = 0.f;
    uint32_t kreg[KREG_TILES][2][4][4];
    __syncthreads();
    asm volatile("barrier.cluster.arrive.relaxed.aligned;" ::: "memory");
    const unsigned epoch = s_flag[0];
    const unsigned base = epoch << 9;

#pragma unroll 1
    for (int s = 0; s < 4; s++) {
        {
            float v[4] = {0.f, 0.f, 0.f, 0.f};
            if (tid < D_MODEL / 4) {
                const uint2 xr = *reinterpret_cast<const uint2*>(xs + tid * 4);
                v[0] = bflo(xr.x); v[1] = bfhi(xr.x); v[2] = bflo(xr.y); v[3] = bfhi(xr.y);
                if (s != 0) {
                    float4 a = __ldcg(reinterpret_cast<const float4*>(&g_acc[s - 1][0][0]) + tid);
#pragma unroll
                    for (int i = 1; i < NREP; i++) {
                        const float4 a2 = __ldcg(reinterpret_cast<const float4*>(&g_acc[s - 1][i][0]) + tid);
                        a.x += a2.x; a.y += a2.y; a.z += a2.z; a.w += a2.w;
                    }
                    a.x = bf16r(a.x); a.y = bf16r(a.y); a.z = bf16r(a.z); a.w = bf16r(a.w);
                    if (s == 2) {
                        const uint2 br = *reinterpret_cast<const uint2*>(b2s + tid * 4);
                        a.x = bf16r(a.x + bflo(br.x)); a.y = bf16r(a.y + bfhi(br.x));
                        a.z = bf16r(a.z + bflo(br.y)); a.w = bf16r(a.w + bfhi(br.y));
                    }
                    v[0] = bf16r(v[0] + a.x); v[1] = bf16r(v[1] + a.y); v[2] = bf16r(v[2] + a.z); v[3] = bf16r(v[3] + a.w);
                    *reinterpret_cast<uint2*>(xs + tid * 4) = make_uint2(pack_bf16(v[0], v[1]), pack_bf16(v[2], v[3]));
                }
            }
            if (s == 2 && b == 0) {
                for (int e = tid; e < NREP * D_MODEL; e += NT) (&g_acc[0][0][0])[e] = 0.f;
            }
#pragma unroll 1
            for (int rep = 0; rep <= (s & 1); rep++) {
                float mean = 0.25f * ((v[0] + v[1]) + (v[2] + v[3]));
                float m2 = (v[0] - mean) * (v[0] - mean) + (v[1] - mean) * (v[1] - mean) +
                           (v[2] - mean) * (v[2] - mean) + (v[3] - mean) * (v[3] - mean);
                float hn = 2.f;
#pragma unroll
                for (int o = 1; o < 32; o <<= 1) {
                    const float mo = __shfl_xor_sync(0xffffffffu, mean, o);
                    const float qo = __shfl_xor_sync(0xffffffffu, m2, o);
                    const float d = mo - mean;
                    m2 = m2 + qo + d * d * hn;
                    mean = 0.5f * (mean + mo);
                    hn *= 2.f;
                }
                float* rd = red + rep * 12;
                if (lane == 0 && w < 5) { rd[2 * w] = mean; rd[2 * w + 1] = m2; }
                __syncthreads();
                float gm = 0.f, gq = 0.f;
#pragma unroll
                for (int i = 0; i < 5; i++) { gm += rd[2 * i]; gq += rd[2 * i + 1]; }
                gm *= 0.2f;
#pragma unroll
                for (int i = 0; i < 5; i++) { const float d = rd[2 * i] - gm; gq += 128.f * d * d; }
                const float mb = bf16r(gm);
                const float den = bf16r(sqrtf(bf16r(bf16r(gq * (1.0f / D_MODEL)) + 1e-5f)));
#pragma unroll
                for (int i = 0; i < 4; i++) v[i] = bf16r(__fdividef(bf16r(v[i] - mb), den));
            }
            if (tid < D_MODEL / 4)
                *reinterpret_cast<uint2*>(xn + tid * 4) = make_uint2(pack_bf16(v[0], v[1]), pack_bf16(v[2], v[3]));
        }
        if (s == 1) cp_async_wait_all();
        __syncthreads();
        float* acc = &g_acc[s][b & (NREP - 1)][0];

        if (!(s & 1)) {
            const int pass = s >> 1;
            mbar_wait(bar_stage, 0);
            {
                float cq[4][4];
#pragma unroll
                for (int i = 0; i < 4; i++) { cq[i][0] = cq[i][1] = cq[i][2] = cq[i][3] = 0.f; }
#pragma unroll
                for (int k5 = 0; k5 < 5; k5++) {
                    const int ks = w * 5 + k5;
                    const uint32_t b0 = *reinterpret_cast<const uint32_t*>(xn + ks * 16 + 2 * t);
                    const uint32_t b1 = *reinterpret_cast<const uint32_t*>(xn + ks * 16 + 2 * t + 8);
                    const int krow = ks * 16 + (lane & 7) + ((lane >> 4) & 1) * 8;
#pragma unroll
                    for (int mt = 0; mt < 4; mt++) {
                        uint32_t a[4];
                        ldmatrix4t(a, sbase + OFF_STAGE + krow * 128 + (((2 * mt + ((lane >> 3) & 1)) ^ (lane & 7)) << 4));
                        mma16816(cq[mt], a[0], a[1], a[2], a[3], b0, b1);
                    }
                }
                if (t == 0) {
#pragma unroll
                    for (int mt = 0; mt < 4; mt++) { oscr[w * 64 + mt * 16 + g] = cq[mt][0]; oscr[w * 64 + mt * 16 + 8 + g] = cq[mt][2]; }
                }
            }
            __syncthreads();
            if (s == 0) asm volatile("barrier.cluster.wait.aligned;" ::: "memory");
            if (tid < 32) {
                float s0 = 0.f, s1 = 0.f;
#pragma unroll
                for (int i = 0; i < 8; i++) { const float2 v2 = *reinterpret_cast<const float2*>(oscr + i * 64 + 2 * tid); s0 += v2.x; s1 += v2.y; }
                const uint32_t qp = pack_bf16(s0, s1);
                *reinterpret_cast<uint32_t*>(qs + r * 64 + 2 * tid) = qp;
                st_async_b32(mapa(sbase + OFF_Q + (r * 64 + 2 * tid) * 2, r ^ 1), qp, mapa(sbase + OFF_XBAR, r ^ 1));
                if (tid == 0) { mbar_expect_tx(sbase + OFF_XBAR, 128); mbar_expect_tx(sbase + OFF_XBAR + 8, 256); }
            }
            const uint32_t vland = sbase + OFF_STAGE + w * (VL * 4096);
#pragma unroll 1
            for (int it = 0; it < VL * 8; it++) {
                const int idx = it * 32 + lane;
                const int row = idx >> 4, ch = idx & 15;
                cp_async16_hint(vland + row * 256 + ((ch ^ (row & 7)) << 4), P.vc + kv_off + row * DH + ch * 8, pol_first);
            }
            cp_async_commit();
            if (s == 0) {
                const bf16* kp = P.kc + kv_off + (g * DH + t * 8);
#pragma unroll
                for (int i = 0; i < KREG_TILES; i++)
#pragma unroll
                    for (int hh = 0; hh < 2; hh++)
#pragma unroll
                        for (int j = 0; j < 4; j++)
                            ldg128_hint(kreg[i][hh][j], kp + (i * 16 + hh * 8) * DH + j * 32, pol_first);
            }
            __syncthreads();
            mbar_wait(sbase + OFF_XBAR, pass);

            float sc[8][2];
            {
                float cacc[KREG_TILES][4];
#pragma unroll
                for (int i = 0; i < KREG_TILES; i++) { cacc[i][0] = cacc[i][1] = cacc[i][2] = cacc[i][3] = 0.f; }
#pragma unroll
                for (int j = 0; j < 4; j++) {
                    const uint4 qv = *reinterpret_cast<const uint4*>(qs + j * 32 + t * 8);
#pragma unroll
                    for (int i = 0; i < KREG_TILES; i++) {
                        mma16816(cacc[i], kreg[i][0][j][0], kreg[i][1][j][0], kreg[i][0][j][1], kreg[i][1][j][1], qv.x, qv.y);
                        mma16816(cacc[i], kreg[i][0][j][2], kreg[i][1][j][2], kreg[i][0][j][3], kreg[i][1][j][3], qv.z, qv.w);
                    }
                }
#pragma unroll
                for (int i = 0; i < KREG_TILES; i++) { sc[i][0] = cacc[i][0]; sc[i][1] = cacc[i][2]; }
            }
            {
                if (s == 0) {
                    if (lane == 0) bulk_prefetch_l2(P.vc + kv_off + VL * 16 * DH, (8 - VL) * 4096);
                    cp_async_wait_group<1>();
                    __syncwarp();
                }
                float cacc[KSM_TILES][4];
#pragma unroll
                for (int tt = 0; tt < KSM_TILES; tt++) { cacc[tt][0] = cacc[tt][1] = cacc[tt][2] = cacc[tt][3] = 0.f; }
                const int row0 = (lane & 7) + ((lane >> 3) & 1) * 8;
#pragma unroll 4
                for (int ks = 0; ks < 8; ks++) {
                    const uint32_t b0 = *reinterpret_cast<const uint32_t*>(qs + ks * 16 + 2 * t);
                    const uint32_t b1 = *reinterpret_cast<const uint32_t*>(qs + ks * 16 + 2 * t + 8);
                    const int ch = 2 * ks + (lane >> 4);
                    const uint32_t ad = kb + row0 * 256 + ((ch ^ (lane & 7)) << 4);
#pragma unroll
                    for (int tt = 0; tt < KSM_TILES; tt++) {
                        uint32_t a[4];
                        ldmatrix4(a, ad + tt * 4096);
                        mma16816(cacc[tt], a[0], a[1], a[2], a[3], b0, b1);
                    }
                }
#pragma unroll
                for (int tt = 0; tt < KSM_TILES; tt++) { sc[KREG_TILES + tt][0] = cacc[tt][0]; sc[KREG_TILES + tt][1] = cacc[tt][2]; }
            }
            bf16* pw = reinterpret_cast<bf16*>(sm + OFF_P + w * 256);
            {
                float s4[4];
#pragma unroll
                for (int q2 = 0; q2 < 4; q2++) {
                    const int i = q2 >> 1, k2 = q2 & 1;
                    const float v01 = (t & 1) ? sc[2 + i][k2] : sc[i][k2];
                    const float v23 = (t & 1) ? sc[6 + i][k2] : sc[4 + i][k2];
                    s4[q2] = (t & 2) ? v23 : v01;
                }
                float mx = -INFINITY;
#pragma unroll
                for (int q2 = 0; q2 < 4; q2++) {
                    s4[q2] = bf16r(bf16r(s4[q2]) * 0.08838834764831845f);
                    mx = fmaxf(mx, s4[q2]);
                }
#pragma unroll
                for (int o = 1; o < 32; o <<= 1) mx = fmaxf(mx, __shfl_xor_sync(0xffffffffu, mx, o));
                float l = 0.f;
#pragma unroll
                for (int q2 = 0; q2 < 4; q2++) {
                    const bf16 pb = __float2bfloat16_rn(ex2((s4[q2] - mx) * LOG2E));
                    l += __bfloat162float(pb);
                    pw[(2 * t + (q2 >> 1)) * 16 + (q2 & 1) * 8 + g] = pb;
                }
                l = warp_sum(l);
                if (lane == 0) { stat[2 * w] = mx; stat[2 * w + 1] = l; }
            }
            __syncthreads();
            float m_cta = stat[0];
#pragma unroll
            for (int i = 1; i < 8; i++) m_cta = fmaxf(m_cta, stat[2 * i]);
            const float wfac = ex2((stat[2 * w] - m_cta) * LOG2E);
            if (tid == 0) {
                float l_cta = 0.f;
#pragma unroll
                for (int i = 0; i < 8; i++) l_cta += stat[2 * i + 1] * ex2((stat[2 * i] - m_cta) * LOG2E);
                asm volatile("st.relaxed.gpu.global.v4.u32 [%0], {%1,%2,%3,%4};" :: "l"(&g_ml[pass][b]),
                             "r"(__float_as_uint(m_cta)), "r"(__float_as_uint(l_cta)), "r"(epoch * 2 + pass + 1), "r"(0u) : "memory");
            }

            {
                const bf16* vbase = P.vc + kv_off + (4 * t) * DH + g * 8;
                float* ow = oscr + w * 128;
                constexpr int NK = 8 - VL;
                static_assert(NK % NVB == 0, "NVB");
                uint32_t vbuf[NVB][4][4];
#pragma unroll
                for (int u = 0; u < NVB - 1; u++)
#pragma unroll
                    for (int i = 0; i < 4; i++) ldg128_hint(vbuf[u][i], vbase + ((VL + u) * 16 + i) * DH, pol_norm);
                cp_async_wait_all();
                __syncwarp();
#pragma unroll 4
                for (int mt = 0; mt < 8; mt++) {
                    float cl[4] = {0.f, 0.f, 0.f, 0.f};
#pragma unroll
                    for (int kt = 0; kt < VL; kt++) {
                        const uint32_t b0 = *reinterpret_cast<const uint32_t*>(pw + kt * 16 + 2 * t);
                        const uint32_t b1 = *reinterpret_cast<const uint32_t*>(pw + kt * 16 + 2 * t + 8);
                        const int row = kt * 16 + (lane & 7) + ((lane >> 4) & 1) * 8;
                        uint32_t a[4];
                        ldmatrix4t(a, vland + row * 256 + (((2 * mt + ((lane >> 3) & 1)) ^ (lane & 7)) << 4));
                        mma16816(cl, a[0], a[1], a[2], a[3], b0, b1);
                    }
                    if (t == 0) { ow[mt * 16 + g] = cl[0] * wfac; ow[mt * 16 + 8 + g] = cl[2] * wfac; }
                }
                __syncwarp();
                if (w != 7) asm volatile("bar.arrive 1, 256;" ::: "memory");
                float oacc[4][4];
#pragma unroll
                for (int i = 0; i < 4; i++) { oacc[i][0] = oacc[i][1] = oacc[i][2] = oacc[i][3] = 0.f; }
#pragma unroll 1
                for (int hf = 0; hf < 2; hf++) {
#pragma unroll 1
                    for (int k0 = 0; k0 < NK; k0 += NVB) {
                        if (w == 7 && hf == 1 && k0 == 2) {
                            asm volatile("bar.sync 1, 256;" ::: "memory");
                            if (lane == 0) {
                                mbar_expect_tx(bar_stage, 81920);
#pragma unroll 1
                                for (int i = 0; i < 10; i++) tma_2d_hint(sbase + OFF_STAGE + i * 8192, &tm_wo, i * 64, h * DH + r * 64, bar_stage, pol_first);
                            }
                            __syncwarp();
                        }
#pragma unroll
                        for (int u = 0; u < NVB; u++) {
                            const int kt = k0 + u;
                            int nk = kt + NVB - 1, nh = hf;
                            if (nk >= NK) { nk -= NK; nh = hf + 1; }
                            if (nh < 2) {
                                const bf16* vp = vbase + (VL + nk) * 16 * DH + nh * 64;
#pragma unroll
                                for (int i = 0; i < 4; i++) ldg128_hint(vbuf[(u + NVB - 1) % NVB][i], vp + i * DH, pol_norm);
                            }
                            const uint2 pb = *reinterpret_cast<const uint2*>(pw + (VL + kt) * 16 + 4 * t);
#pragma unroll
                            for (int e = 0; e < 4; e++)
                                mma16816(oacc[e], __byte_perm(vbuf[u][0][e], vbuf[u][1][e], 0x5410), __byte_perm(vbuf[u][0][e], vbuf[u][1][e], 0x7632),
                                         __byte_perm(vbuf[u][2][e], vbuf[u][3][e], 0x5410), __byte_perm(vbuf[u][2][e], vbuf[u][3][e], 0x7632), pb.x, pb.y);
                        }
                    }
                    if (t == 0) {
                        float* o2 = ow + hf * 64 + g * 8;
                        float4 u0 = *reinterpret_cast<float4*>(o2), u1 = *reinterpret_cast<float4*>(o2 + 4);
                        u0.x += oacc[0][0] * wfac; u0.y += oacc[0][2] * wfac; u0.z += oacc[1][0] * wfac; u0.w += oacc[1][2] * wfac;
                        u1.x += oacc[2][0] * wfac; u1.y += oacc[2][2] * wfac; u1.z += oacc[3][0] * wfac; u1.w += oacc[3][2] * wfac;
                        *reinterpret_cast<float4*>(o2) = u0;
                        *reinterpret_cast<float4*>(o2 + 4) = u1;
                    }
#pragma unroll
                    for (int i = 0; i < 4; i++) { oacc[i][0] = oacc[i][1] = oacc[i][2] = oacc[i][3] = 0.f; }
                }
            }
            if (s == 0 && b < MLP_CTAS) {
#pragma unroll 1
                for (int idx = tid; idx < 2 * D_MODEL; idx += NT) {
                    const int row = idx >> 1, hf = idx & 1;
                    cp_async16_hint(sbase + OFF_W1 + row * 32 + hf * 16, P.w1 + (size_t)row * FF + b * MLP_UNITS + hf * 8, pol_first);
                    const int r2 = idx / 80, ch = idx - r2 * 80;
                    cp_async16_hint(sbase + OFF_W2 + r2 * 1280 + ((ch ^ (r2 & 7)) << 4), P.w2 + (size_t)(b * MLP_UNITS) * D_MODEL + idx * 8, pol_first);
                }
                cp_async_commit();
            }
            __syncthreads();
            if (tid < 128) {
                uint4 rec[4];
                {
                    unsigned it = 0;
                    const unsigned tag = epoch * 2 + pass + 1;
                    while (true) {
#pragma unroll
                        for (int i = 0; i < 4; i++)
                            asm volatile("ld.relaxed.gpu.global.v4.u32 {%0,%1,%2,%3}, [%4];"
                                         : "=r"(rec[i].x), "=r"(rec[i].y), "=r"(rec[i].z), "=r"(rec[i].w)
                                         : "l"(&g_ml[pass][(b & ~3) + i]) : "memory");
                        if (rec[0].z == tag && rec[1].z == tag && rec[2].z == tag && rec[3].z == tag) break;
                        if (++it > SPIN_LIMIT) __trap();
                    }
                }
                const float M = fmaxf(fmaxf(__uint_as_float(rec[0].x), __uint_as_float(rec[1].x)),
                                      fmaxf(__uint_as_float(rec[2].x), __uint_as_float(rec[3].x)));
                float L = 0.f;
#pragma unroll
                for (int i = 0; i < 4; i++) L += __uint_as_float(rec[i].y) * ex2((__uint_as_float(rec[i].x) - M) * LOG2E);
                const float scale = __fdividef(ex2((m_cta - M) * LOG2E), L);
                float sum = 0.f;
#pragma unroll
                for (int i = 0; i < 8; i++) sum += oscr[i * 128 + tid];
                if ((tid >> 6) == r) oex[r * 64 + (tid & 63)] = sum * scale;
                else st_async_b32(mapa(sbase + OFF_OEX + (r * 64 + (tid & 63)) * 4, r ^ 1), __float_as_uint(sum * scale), mapa(sbase + OFF_XBAR + 8, r ^ 1));
            }
            __syncthreads();
            if (tid < 64) {
                mbar_wait(sbase + OFF_XBAR + 8, pass);
                const float o = oex[tid] + oex[64 + tid];
                const bf16 hi = __float2bfloat16_rn(o);
                hs[32 + tid] = hi;
                hs[96 + tid] = __float2bfloat16_rn(o - __bfloat162float(hi));
            }
            mbar_wait(bar_stage, 1);
            __syncthreads();
            {
                float co[5][4];
#pragma unroll
                for (int i = 0; i < 5; i++) { co[i][0] = co[i][1] = co[i][2] = co[i][3] = 0.f; }
#pragma unroll 1
                for (int ks = 0; ks < 4; ks++) {
                    uint32_t b0 = 0, b1 = 0;
                    if (g < 2) {
                        b0 = *reinterpret_cast<const uint32_t*>(hs + 32 + g * 64 + ks * 16 + 2 * t);
                        b1 = *reinterpret_cast<const uint32_t*>(hs + 32 + g * 64 + ks * 16 + 2 * t + 8);
                    }
                    const int krow = ks * 16 + (lane & 7) + ((lane >> 4) & 1) * 8;
#pragma unroll
                    for (int i = 0; i < 5; i++) {
                        const int ch = 2 * (w * 5 + i) + ((lane >> 3) & 1);
                        uint32_t a[4];
                        ldmatrix4t(a, sbase + OFF_STAGE + (ch >> 3) * 8192 + krow * 128 + (((ch ^ lane) & 7) << 4));
                        mma16816(co[i], a[0], a[1], a[2], a[3], b0, b1);
                    }
                }
                if (t == 0) {
#pragma unroll
                    for (int i = 0; i < 5; i++) {
                        oscr[(w * 5 + i) * 16 + g] = co[i][0] + co[i][1];
                        oscr[(w * 5 + i) * 16 + 8 + g] = co[i][2] + co[i][3];
                    }
                }
                __syncwarp();
                if (lane < 20) {
                    const float4 v4 = *reinterpret_cast<const float4*>(oscr + w * 80 + lane * 4);
                    red_add_v4(acc + w * 80 + lane * 4, v4.x, v4.y, v4.z, v4.w);
                }
            }
            if (s == 0) {
                __syncthreads();
                if (tid == 224) {
                    mbar_expect_tx(bar_stage, 81920);
#pragma unroll 1
                    for (int i = 0; i < 5; i++) tma_2d_hint(sbase + OFF_STAGE + i * 16384, &tm_wq, h * DH + r * 64, i * 128, bar_stage, pol_first);
                }
            }
        } else if (b < MLP_CTAS) {
            {
                float ch4[4] = {0.f, 0.f, 0.f, 0.f};
#pragma unroll
                for (int k5 = 0; k5 < 5; k5++) {
                    const int ks = w * 5 + k5;
                    const uint32_t b0 = *reinterpret_cast<const uint32_t*>(xn + ks * 16 + 2 * t);
                    const uint32_t b1 = *reinterpret_cast<const uint32_t*>(xn + ks * 16 + 2 * t + 8);
                    const int krow = ks * 16 + (lane & 7) + ((lane >> 4) & 1) * 8;
                    uint32_t a[4];
                    ldmatrix4t(a, sbase + OFF_W1 + krow * 32 + ((lane >> 3) & 1) * 16);
                    mma16816(ch4, a[0], a[1], a[2], a[3], b0, b1);
                }
                if (t == 0) { oscr[w * 16 + g] = ch4[0]; oscr[w * 16 + 8 + g] = ch4[2]; }
            }
            __syncthreads();
            if (tid < 16) {
                float sum = 0.f;
#pragma unroll
                for (int i = 0; i < 8; i++) sum += oscr[i * 16 + tid];
                const float u = bf16r(bf16r(sum) + __bfloat162float(hs[16 + tid]));
                const float inner = 0.7978845608028654f * (u + 0.044715f * u * u * u);
                const float th = 1.0f - __fdividef(2.0f, ex2(inner * (2.0f * LOG2E)) + 1.0f);
                hs[tid] = __float2bfloat16_rn(0.5f * u * (1.0f + th));
            }
            __syncthreads();
            {
                const uint32_t b0 = *reinterpret_cast<const uint32_t*>(hs + 2 * t);
                const uint32_t b1 = *reinterpret_cast<const uint32_t*>(hs + 2 * t + 8);
                const int krow = (lane & 7) + ((lane >> 4) & 1) * 8;
#pragma unroll
                for (int i = 0; i < 5; i++) {
                    const int ch = 2 * (w * 5 + i) + ((lane >> 3) & 1);
                    uint32_t a[4];
                    float co[4] = {0.f, 0.f, 0.f, 0.f};
                    ldmatrix4t(a, sbase + OFF_W2 + krow * 1280 + ((ch ^ (lane & 7)) << 4));
                    mma16816(co, a[0], a[1], a[2], a[3], b0, b1);
                    if (t == 0) {
                        oscr[256 + (w * 5 + i) * 16 + g] = co[0];
                        oscr[256 + (w * 5 + i) * 16 + 8 + g] = co[2];
                    }
                }
                __syncwarp();
                if (lane < 20) {
                    const float4 v4 = *reinterpret_cast<const float4*>(oscr + 256 + w * 80 + lane * 4);
                    red_add_v4(acc + w * 80 + lane * 4, v4.x, v4.y, v4.z, v4.w);
                }
            }
        }
        if (s < 3) grid_barrier(base + NCTA * (s + 1));
    }
    __syncthreads();
    if (tid == 0) {
        __threadfence();
        const unsigned old = atomicAdd(&g_ctr, 1u);
        s_flag[1] = (old == base + 4 * NCTA - 1) ? 1u : 0u;
        __threadfence();
    }
    __syncthreads();
    if (s_flag[1]) {
        for (int e = tid; e < D_MODEL; e += NT) {
            float a = 0.f;
#pragma unroll
            for (int i = 0; i < NREP; i++) a += __ldcg(&g_acc[3][i][e]);
            const float o = bf16r(bf16r(a) + __bfloat162float(b2s[e]));
            P.out[e] = __float2bfloat16_rn(__bfloat162float(xs[e]) + o);
        }
    }
}

}

extern "C" void kernel_launch(void* const* d_in, const int* in_sizes, int n_in,
                              void* d_out, int out_size) {
    Params P;
    P.x = (const bf16*)d_in[0];
    P.kc = (const bf16*)d_in[1];
    P.vc = (const bf16*)d_in[2];
    P.wq = (const bf16*)d_in[3];
    P.wo = (const bf16*)d_in[4];
    P.w1 = (const bf16*)d_in[6];
    P.b1 = (const bf16*)d_in[7];
    P.w2 = (const bf16*)d_in[8];
    P.b2 = (const bf16*)d_in[9];
    P.out = (bf16*)d_out;

    cudaFuncSetAttribute(fused_kernel, cudaFuncAttributeMaxDynamicSharedMemorySize, SMEM_BYTES);

    typedef CUresult (*EncodeFn)(CUtensorMap*, CUtensorMapDataType, cuuint32_t, void*, const cuuint64_t*, const cuuint64_t*,
                                 const cuuint32_t*, const cuuint32_t*, CUtensorMapInterleave, CUtensorMapSwizzle,
                                 CUtensorMapL2promotion, CUtensorMapFloatOOBfill);
    void* fn = nullptr;
    cudaDriverEntryPointQueryResult qres;
    cudaGetDriverEntryPoint("cuTensorMapEncodeTiled", &fn, cudaEnableDefault, &qres);
    EncodeFn encode = (EncodeFn)fn;
    CUtensorMap tm_wq, tm_wo;
    {
        cuuint64_t dims[2] = {(cuuint64_t)(NHEAD * DH), (cuuint64_t)D_MODEL};
        cuuint64_t strides[1] = {(cuuint64_t)(NHEAD * DH * 2)};
        cuuint32_t box[2] = {64, 128};
        cuuint32_t es[2] = {1, 1};
        encode(&tm_wq, CU_TENSOR_MAP_DATA_TYPE_BFLOAT16, 2, (void*)P.wq, dims, strides, box, es, CU_TENSOR_MAP_INTERLEAVE_NONE,
               CU_TENSOR_MAP_SWIZZLE_128B, CU_TENSOR_MAP_L2_PROMOTION_NONE, CU_TENSOR_MAP_FLOAT_OOB_FILL_NONE);
    }
    {
        cuuint64_t dims[2] = {(cuuint64_t)D_MODEL, (cuuint64_t)(NHEAD * DH)};
        cuuint64_t strides[1] = {(cuuint64_t)(D_MODEL * 2)};
        cuuint32_t box[2] = {64, 64};
        cuuint32_t es[2] = {1, 1};
        encode(&tm_wo, CU_TENSOR_MAP_DATA_TYPE_BFLOAT16, 2, (void*)P.wo, dims, strides, box, es, CU_TENSOR_MAP_INTERLEAVE_NONE,
               CU_TENSOR_MAP_SWIZZLE_128B, CU_TENSOR_MAP_L2_PROMOTION_NONE, CU_TENSOR_MAP_FLOAT_OOB_FILL_NONE);
    }

    cudaLaunchConfig_t cfg = {};
    cfg.gridDim = dim3(NCTA);
    cfg.blockDim = dim3(NT);
    cfg.dynamicSmemBytes = SMEM_BYTES;
    cfg.stream = cudaStreamPerThread;
    cudaLaunchAttribute at[2];
    at[0].id = cudaLaunchAttributeClusterDimension;
    at[0].val.clusterDim.x = 2; at[0].val.clusterDim.y = 1; at[0].val.clusterDim.z = 1;
    at[1].id = cudaLaunchAttributeCooperative;
    at[1].val.cooperative = 1;
    cfg.attrs = at;
    cfg.numAttrs = 2;
    cudaLaunchKernelEx(&cfg, fused_kernel, P, tm_wq, tm_wo);
}
```

```cpp
#include <cuda_runtime.h>
#include <cuda.h>
#include <cuda_bf16.h>
#include <stdint.h>

typedef __nv_bfloat16 bf16;

namespace {

constexpr int D_MODEL = 640;
constexpr int NHEAD = 32;
constexpr int SEQ = 4096;
constexpr int DH = 128;
constexpr int FF = 1728;
constexpr int NCTA = 128;
constexpr int NT = 256;
constexpr int KREG_TILES = 5;
constexpr int KSM_TILES = 3;
constexpr int MLP_UNITS = 16;
constexpr int MLP_CTAS = FF / MLP_UNITS;

constexpr int OFF_STAGE = 0;
constexpr int OFF_W2 = 81920;
constexpr int OFF_W1 = OFF_W2 + 20480;
constexpr int OFF_K = OFF_W1 + 20480;
constexpr int OFF_XS = OFF_K + 98304;
constexpr int OFF_XN = OFF_XS + 1280;
constexpr int OFF_O = OFF_XN + 1280;
constexpr int OFF_P = OFF_O + 4096;
constexpr int OFF_Q = OFF_P + 2048;
constexpr int OFF_OEX = OFF_Q + 256;
constexpr int OFF_STAT = OFF_OEX + 512;
constexpr int OFF_RED = OFF_STAT + 80;
constexpr int OFF_HS = OFF_RED + 96;
constexpr int OFF_B2 = OFF_HS + 320;
constexpr int OFF_XBAR = OFF_B2 + 1280;
constexpr int SMEM_BYTES = OFF_XBAR + 16;

static_assert(SMEM_BYTES <= 232448, "smem");
constexpr int NREP = 8;
constexpr int VL = 2;
constexpr int NVB = 2;
constexpr unsigned SPIN_LIMIT = 1u << 24;

__device__ unsigned int g_ctr;
__device__ float g_acc[4][NREP][D_MODEL];
__device__ uint4 g_ml[2][NCTA];

struct Params {
    const bf16* x; const bf16* kc; const bf16* vc; const bf16* wq; const bf16* wo;
    const bf16* w1; const bf16* b1; const bf16* w2; const bf16* b2; bf16* out;
};

__device__ __forceinline__ float bf16r(float x) { return __bfloat162float(__float2bfloat16_rn(x)); }
__device__ __forceinline__ float bflo(uint32_t u) { return __uint_as_float(u << 16); }
__device__ __forceinline__ float bfhi(uint32_t u) { return __uint_as_float(u & 0xffff0000u); }

__device__ __forceinline__ uint32_t smem_u32(const void* p) { return (uint32_t)__cvta_generic_to_shared(p); }

__device__ __forceinline__ void mbar_init(uint32_t bar, uint32_t cnt) {
    asm volatile("mbarrier.init.shared::cta.b64 [%0], %1;" :: "r"(bar), "r"(cnt) : "memory");
}
__device__ __forceinline__ void mbar_expect_tx(uint32_t bar, uint32_t bytes) {
    asm volatile("mbarrier.arrive.expect_tx.shared::cta.b64 _, [%0], %1;" :: "r"(bar), "r"(bytes) : "memory");
}
__device__ __forceinline__ void mbar_wait(uint32_t bar, uint32_t parity) {
    unsigned it = 0;
    while (true) {
        uint32_t ok;
        asm volatile("{\n\t.reg .pred p;\n\tmbarrier.try_wait.parity.shared::cta.b64 p, [%1], %2;\n\tselp.u32 %0, 1, 0, p;\n\t}"
                     : "=r"(ok) : "r"(bar), "r"(parity) : "memory");
        if (ok) break;
        if (++it > SPIN_LIMIT) __trap();
    }
}
__device__ __forceinline__ void tma_2d_hint(uint32_t dst, const CUtensorMap* tm, int c0, int c1, uint32_t bar, uint64_t pol) {
    asm volatile("cp.async.bulk.tensor.2d.shared::cluster.global.mbarrier::complete_tx::bytes.L2::cache_hint [%0], [%1, {%3, %4}], [%2], %5;"
                 :: "r"(dst), "l"(tm), "r"(bar), "r"(c0), "r"(c1), "l"(pol) : "memory");
}
__device__ __forceinline__ void bulk_prefetch_l2(const void* src, uint32_t bytes) {
    asm volatile("cp.async.bulk.prefetch.L2.global [%0], %1;" :: "l"(src), "r"(bytes) : "memory");
}
__device__ __forceinline__ float ex2(float x) { float y; asm("ex2.approx.ftz.f32 %0, %1;" : "=f"(y) : "f"(x)); return y; }
__device__ __forceinline__ void cp_async16_hint(uint32_t dst, const void* src, uint64_t pol) {
    asm volatile("cp.async.cg.shared.global.L2::cache_hint [%0], [%1], 16, %2;" :: "r"(dst), "l"(src), "l"(pol) : "memory");
}
__device__ __forceinline__ void cp_async_wait_all() { asm volatile("cp.async.wait_all;" ::: "memory"); }
__device__ __forceinline__ void cp_async_commit() { asm volatile("cp.async.commit_group;" ::: "memory"); }
template <int N> __device__ __forceinline__ void cp_async_wait_group() { asm volatile("cp.async.wait_group %0;" :: "n"(N) : "memory"); }

__device__ __forceinline__ void ldg128_hint(uint32_t (&r)[4], const void* p, uint64_t pol) {
    asm volatile("ld.global.nc.L1::no_allocate.L2::cache_hint.v4.u32 {%0,%1,%2,%3}, [%4], %5;"
                 : "=r"(r[0]), "=r"(r[1]), "=r"(r[2]), "=r"(r[3]) : "l"(p), "l"(pol));
}
__device__ __forceinline__ void mma16816(float (&c)[4], uint32_t a0, uint32_t a1, uint32_t a2, uint32_t a3,
                                         uint32_t b0, uint32_t b1) {
    asm volatile("mma.sync.aligned.m16n8k16.row.col.f32.bf16.bf16.f32 {%0,%1,%2,%3}, {%4,%5,%6,%7}, {%8,%9}, {%0,%1,%2,%3};"
                 : "+f"(c[0]), "+f"(c[1]), "+f"(c[2]), "+f"(c[3])
                 : "r"(a0), "r"(a1), "r"(a2), "r"(a3), "r"(b0), "r"(b1));
}
__device__ __forceinline__ void ldmatrix4(uint32_t (&r)[4], uint32_t addr) {
    asm volatile("ldmatrix.sync.aligned.m8n8.x4.shared.b16 {%0,%1,%2,%3}, [%4];"
                 : "=r"(r[0]), "=r"(r[1]), "=r"(r[2]), "=r"(r[3]) : "r"(addr) : "memory");
}
__device__ __forceinline__ void red_add_v4(float* p, float a, float b, float c, float d) {
    asm volatile("red.global.add.v4.f32 [%0], {%1,%2,%3,%4};" :: "l"(p), "f"(a), "f"(b), "f"(c), "f"(d) : "memory");
}
__device__ __forceinline__ unsigned ld_acquire(const unsigned* p) {
    unsigned v; asm volatile("ld.acquire.gpu.global.u32 %0, [%1];" : "=r"(v) : "l"(p) : "memory"); return v;
}
__device__ __forceinline__ uint32_t mapa(uint32_t addr, uint32_t rank) {
    uint32_t r; asm volatile("mapa.shared::cluster.u32 %0, %1, %2;" : "=r"(r) : "r"(addr), "r"(rank)); return r;
}
__device__ __forceinline__ void st_async_b32(uint32_t addr, uint32_t v, uint32_t bar) {
    asm volatile("st.async.weak.shared::cluster.mbarrier::complete_tx::bytes.b32 [%0], %1, [%2];" :: "r"(addr), "r"(v), "r"(bar) : "memory");
}
__device__ __forceinline__ float warp_sum(float v) {
#pragma unroll
    for (int o = 16; o > 0; o >>= 1) v += __shfl_xor_sync(0xffffffffu, v, o);
    return v;
}

__device__ __forceinline__ void grid_barrier(unsigned target) {
    __syncthreads();
    if (threadIdx.x == 0) {
        __threadfence();
        atomicAdd(&g_ctr, 1u);
        unsigned it = 0;
        while ((int)(ld_acquire(&g_ctr) - target) < 0) { if (++it > SPIN_LIMIT) __trap(); }
    }
    __syncthreads();
}

constexpr float LOG2E = 1.4426950408889634f;

__device__ __forceinline__ void ldmatrix4t(uint32_t (&r)[4], uint32_t addr) {
    asm volatile("ldmatrix.sync.aligned.m8n8.x4.trans.shared.b16 {%0,%1,%2,%3}, [%4];"
                 : "=r"(r[0]), "=r"(r[1]), "=r"(r[2]), "=r"(r[3]) : "r"(addr) : "memory");
}
__device__ __forceinline__ uint32_t pack_bf16(float lo, float hi) {
    uint32_t r; asm("cvt.rn.bf16x2.f32 %0, %1, %2;" : "=r"(r) : "f"(hi), "f"(lo)); return r;
}

__global__ void __launch_bounds__(NT, 1) fused_kernel(const Params P, const __grid_constant__ CUtensorMap tm_wq,
                                                        const __grid_constant__ CUtensorMap tm_wo) {
    extern __shared__ __align__(1024) unsigned char sm[];
    const int tid = threadIdx.x, lane = tid & 31, w = tid >> 5;
    const int g = lane >> 2, t = lane & 3;
    const int b = blockIdx.x, h = b >> 2, c = b & 3, r = b & 1;
    const uint32_t sbase = smem_u32(sm);
    bf16* xs = reinterpret_cast<bf16*>(sm + OFF_XS);
    bf16* xn = reinterpret_cast<bf16*>(sm + OFF_XN);
    bf16* b2s = reinterpret_cast<bf16*>(sm + OFF_B2);
    float* oscr = reinterpret_cast<float*>(sm + OFF_O);
    bf16* qs = reinterpret_cast<bf16*>(sm + OFF_Q);
    float* oex = reinterpret_cast<float*>(sm + OFF_OEX);
    float* stat = reinterpret_cast<float*>(sm + OFF_STAT);
    float* red = reinterpret_cast<float*>(sm + OFF_RED);
    bf16* hs = reinterpret_cast<bf16*>(sm + OFF_HS);
    volatile unsigned* s_flag = reinterpret_cast<volatile unsigned*>(sm + OFF_STAT + 64);
    const uint32_t bar_stage = sbase + OFF_STAT + 72;
    uint4 sv = make_uint4(0, 0, 0, 0);
    if (tid < D_MODEL / 8) sv = __ldg(reinterpret_cast<const uint4*>(P.x) + tid);
    else if (tid < D_MODEL / 4) sv = __ldg(reinterpret_cast<const uint4*>(P.b2) + (tid - 80));
    else if (tid < 162) { if (b < MLP_CTAS) sv = __ldg(reinterpret_cast<const uint4*>(P.b1 + b * MLP_UNITS) + (tid - 160)); }
    else if (tid == 192) sv.x = ld_acquire(&g_ctr) >> 9;
    uint64_t pol_first;
    asm volatile("createpolicy.fractional.L2::evict_first.b64 %0, 1.0;" : "=l"(pol_first));
    uint64_t pol_norm;
    asm volatile("createpolicy.fractional.L2::evict_normal.b64 %0, 1.0;" : "=l"(pol_norm));

    const size_t kv_off = (size_t)(h * SEQ + c * 1024 + w * 128) * DH;
    if (tid == 224) {
        mbar_init(bar_stage, 1);
        mbar_init(sbase + OFF_XBAR, 1);
        mbar_init(sbase + OFF_XBAR + 8, 1);
        asm volatile("fence.mbarrier_init.release.cluster;" ::: "memory");
        asm volatile("fence.proxy.async.shared::cta;" ::: "memory");
        mbar_expect_tx(bar_stage, 81920);
#pragma unroll
        for (int i = 0; i < 5; i++) tma_2d_hint(sbase + OFF_STAGE + i * 16384, &tm_wq, h * DH + r * 64, i * 128, bar_stage, pol_first);
    }
    const uint32_t kb = sbase + OFF_K + w * (KSM_TILES * 16 * 256);
    {
        const bf16* kq = P.kc + kv_off + KREG_TILES * 16 * DH;
#pragma unroll 1
        for (int it = 0; it < KSM_TILES * 8; it++) {
            const int idx = it * 32 + lane;
            const int row = idx >> 4, ch = idx & 15;
            cp_async16_hint(kb + row * 256 + ((ch ^ (row & 7)) << 4), kq + row * DH + ch * 8, pol_first);
        }
    }
    cp_async_commit();
    if (tid < D_MODEL / 8) *reinterpret_cast<uint4*>(xs + tid * 8) = sv;
    else if (tid < D_MODEL / 4) *reinterpret_cast<uint4*>(b2s + (tid - 80) * 8) = sv;
    else if (tid < 162) *reinterpret_cast<uint4*>(hs + 16 + (tid - 160) * 8) = sv;
    else if (tid == 192) s_flag[0] = sv.x;
    if (b == 1) for (int e = tid; e < 3 * NREP * D_MODEL; e += NT) (&g_acc[1][0][0])[e] = 0.f;
    uint32_t kreg[KREG_TILES][2][4][4];
    __syncthreads();
    asm volatile("barrier.cluster.arrive.relaxed.aligned;" ::: "memory");
    const unsigned epoch = s_flag[0];
    const unsigned base = epoch << 9;

#pragma unroll 1
    for (int s = 0; s < 4; s++) {
        {
            float v[4] = {0.f, 0.f, 0.f, 0.f};
            if (tid < D_MODEL / 4) {
                const uint2 xr = *reinterpret_cast<const uint2*>(xs + tid * 4);
                v[0] = bflo(xr.x); v[1] = bfhi(xr.x); v[2] = bflo(xr.y); v[3] = bfhi(xr.y);
                if (s != 0) {
                    float4 a = __ldcg(reinterpret_cast<const float4*>(&g_acc[s - 1][0][0]) + tid);
#pragma unroll
                    for (int i = 1; i < NREP; i++) {
                        const float4 a2 = __ldcg(reinterpret_cast<const float4*>(&g_acc[s - 1][i][0]) + tid);
                        a.x += a2.x; a.y += a2.y; a.z += a2.z; a.w += a2.w;
                    }
                    a.x = bf16r(a.x); a.y = bf16r(a.y); a.z = bf16r(a.z); a.w = bf16r(a.w);
                    if (s == 2) {
                        const uint2 br = *reinterpret_cast<const uint2*>(b2s + tid * 4);
                        a.x = bf16r(a.x + bflo(br.x)); a.y = bf16r(a.y + bfhi(br.x));
                        a.z = bf16r(a.z + bflo(br.y)); a.w = bf16r(a.w + bfhi(br.y));
                    }
                    v[0] = bf16r(v[0] + a.x); v[1] = bf16r(v[1] + a.y); v[2] = bf16r(v[2] + a.z); v[3] = bf16r(v[3] + a.w);
                    *reinterpret_cast<uint2*>(xs + tid * 4) = make_uint2(pack_bf16(v[0], v[1]), pack_bf16(v[2], v[3]));
                }
            }
            if (s == 2 && b == 0) {
                for (int e = tid; e < NREP * D_MODEL; e += NT) (&g_acc[0][0][0])[e] = 0.f;
            }
#pragma unroll 1
            for (int rep = 0; rep <= (s & 1); rep++) {
                float mean = 0.25f * ((v[0] + v[1]) + (v[2] + v[3]));
                float m2 = (v[0] - mean) * (v[0] - mean) + (v[1] - mean) * (v[1] - mean) +
                           (v[2] - mean) * (v[2] - mean) + (v[3] - mean) * (v[3] - mean);
                float hn = 2.f;
#pragma unroll
                for (int o = 1; o < 32; o <<= 1) {
                    const float mo = __shfl_xor_sync(0xffffffffu, mean, o);
                    const float qo = __shfl_xor_sync(0xffffffffu, m2, o);
                    const float d = mo - mean;
                    m2 = m2 + qo + d * d * hn;
                    mean = 0.5f * (mean + mo);
                    hn *= 2.f;
                }
                float* rd = red + rep * 12;
                if (lane == 0 && w < 5) { rd[2 * w] = mean; rd[2 * w + 1] = m2; }
                __syncthreads();
                float gm = 0.f, gq = 0.f;
#pragma unroll
                for (int i = 0; i < 5; i++) { gm += rd[2 * i]; gq += rd[2 * i + 1]; }
                gm *= 0.2f;
#pragma unroll
                for (int i = 0; i < 5; i++) { const float d = rd[2 * i] - gm; gq += 128.f * d * d; }
                const float mb = bf16r(gm);
                const float den = bf16r(sqrtf(bf16r(bf16r(gq * (1.0f / D_MODEL)) + 1e-5f)));
#pragma unroll
                for (int i = 0; i < 4; i++) v[i] = bf16r(__fdividef(bf16r(v[i] - mb), den));
            }
            if (tid < D_MODEL / 4)
                *reinterpret_cast<uint2*>(xn + tid * 4) = make_uint2(pack_bf16(v[0], v[1]), pack_bf16(v[2], v[3]));
        }
        if (s == 1) cp_async_wait_all();
        __syncthreads();
        float* acc = &g_acc[s][b & (NREP - 1)][0];

        if (!(s & 1)) {
            const int pass = s >> 1;
            mbar_wait(bar_stage, 0);
            {
                float cq[4][4];
#pragma unroll
                for (int i = 0; i < 4; i++) { cq[i][0] = cq[i][1] = cq[i][2] = cq[i][3] = 0.f; }
#pragma unroll
                for (int k5 = 0; k5 < 5; k5++) {
                    const int ks = w * 5 + k5;
                    const uint32_t b0 = *reinterpret_cast<const uint32_t*>(xn + ks * 16 + 2 * t);
                    const uint32_t b1 = *reinterpret_cast<const uint32_t*>(xn + ks * 16 + 2 * t + 8);
                    const int krow = ks * 16 + (lane & 7) + ((lane >> 4) & 1) * 8;
#pragma unroll
                    for (int mt = 0; mt < 4; mt++) {
                        uint32_t a[4];
                        ldmatrix4t(a, sbase + OFF_STAGE + krow * 128 + (((2 * mt + ((lane >> 3) & 1)) ^ (lane & 7)) << 4));
                        mma16816(cq[mt], a[0], a[1], a[2], a[3], b0, b1);
                    }
                }
                if (t == 0) {
#pragma unroll
                    for (int mt = 0; mt < 4; mt++) { oscr[w * 64 + mt * 16 + g] = cq[mt][0]; oscr[w * 64 + mt * 16 + 8 + g] = cq[mt][2]; }
                }
            }
            __syncthreads();
            if (s == 0) asm volatile("barrier.cluster.wait.aligned;" ::: "memory");
            if (tid < 32) {
                float s0 = 0.f, s1 = 0.f;
#pragma unroll
                for (int i = 0; i < 8; i++) { const float2 v2 = *reinterpret_cast<const float2*>(oscr + i * 64 + 2 * tid); s0 += v2.x; s1 += v2.y; }
                const uint32_t qp = pack_bf16(s0, s1);
                *reinterpret_cast<uint32_t*>(qs + r * 64 + 2 * tid) = qp;
                st_async_b32(mapa(sbase + OFF_Q + (r * 64 + 2 * tid) * 2, r ^ 1), qp, mapa(sbase + OFF_XBAR, r ^ 1));
                if (tid == 0) { mbar_expect_tx(sbase + OFF_XBAR, 128); mbar_expect_tx(sbase + OFF_XBAR + 8, 256); }
            }
            const uint32_t vland = sbase + OFF_STAGE + w * (VL * 4096);
#pragma unroll 1
            for (int it = 0; it < VL * 8; it++) {
                const int idx = it * 32 + lane;
                const int row = idx >> 4, ch = idx & 15;
                cp_async16_hint(vland + row * 256 + ((ch ^ (row & 7)) << 4), P.vc + kv_off + row * DH + ch * 8, pol_first);
            }
            cp_async_commit();
            if (s == 0) {
                const bf16* kp = P.kc + kv_off + (g * DH + t * 8);
#pragma unroll
                for (int i = 0; i < KREG_TILES; i++)
#pragma unroll
                    for (int hh = 0; hh < 2; hh++)
#pragma unroll
                        for (int j = 0; j < 4; j++)
                            ldg128_hint(kreg[i][hh][j], kp + (i * 16 + hh * 8) * DH + j * 32, pol_first);
            }
            __syncthreads();
            mbar_wait(sbase + OFF_XBAR, pass);

            float sc[8][2];
            {
                float cacc[KREG_TILES][4];
#pragma unroll
                for (int i = 0; i < KREG_TILES; i++) { cacc[i][0] = cacc[i][1] = cacc[i][2] = cacc[i][3] = 0.f; }
#pragma unroll
                for (int j = 0; j < 4; j++) {
                    const uint4 qv = *reinterpret_cast<const uint4*>(qs + j * 32 + t * 8);
#pragma unroll
                    for (int i = 0; i < KREG_TILES; i++) {
                        mma16816(cacc[i], kreg[i][0][j][0], kreg[i][1][j][0], kreg[i][0][j][1], kreg[i][1][j][1], qv.x, qv.y);
                        mma16816(cacc[i], kreg[i][0][j][2], kreg[i][1][j][2], kreg[i][0][j][3], kreg[i][1][j][3], qv.z, qv.w);
                    }
                }
#pragma unroll
                for (int i = 0; i < KREG_TILES; i++) { sc[i][0] = cacc[i][0]; sc[i][1] = cacc[i][2]; }
            }
            {
                if (s == 0) {
                    if (lane == 0) bulk_prefetch_l2(P.vc + kv_off + VL * 16 * DH, (8 - VL) * 4096);
                    cp_async_wait_group<1>();
                    __syncwarp();
                }
                float cacc[KSM_TILES][4];
#pragma unroll
                for (int tt = 0; tt < KSM_TILES; tt++) { cacc[tt][0] = cacc[tt][1] = cacc[tt][2] = cacc[tt][3] = 0.f; }
                const int row0 = (lane & 7) + ((lane >> 3) & 1) * 8;
#pragma unroll 4
                for (int ks = 0; ks < 8; ks++) {
                    const uint32_t b0 = *reinterpret_cast<const uint32_t*>(qs + ks * 16 + 2 * t);
                    const uint32_t b1 = *reinterpret_cast<const uint32_t*>(qs + ks * 16 + 2 * t + 8);
                    const int ch = 2 * ks + (lane >> 4);
                    const uint32_t ad = kb + row0 * 256 + ((ch ^ (lane & 7)) << 4);
#pragma unroll
                    for (int tt = 0; tt < KSM_TILES; tt++) {
                        uint32_t a[4];
                        ldmatrix4(a, ad + tt * 4096);
                        mma16816(cacc[tt], a[0], a[1], a[2], a[3], b0, b1);
                    }
                }
#pragma unroll
                for (int tt = 0; tt < KSM_TILES; tt++) { sc[KREG_TILES + tt][0] = cacc[tt][0]; sc[KREG_TILES + tt][1] = cacc[tt][2]; }
            }
            bf16* pw = reinterpret_cast<bf16*>(sm + OFF_P + w * 256);
            {
                float s4[4];
#pragma unroll
                for (int q2 = 0; q2 < 4; q2++) {
                    const int i = q2 >> 1, k2 = q2 & 1;
                    const float v01 = (t & 1) ? sc[2 + i][k2] : sc[i][k2];
                    const float v23 = (t & 1) ? sc[6 + i][k2] : sc[4 + i][k2];
                    s4[q2] = (t & 2) ? v23 : v01;
                }
                float mx = -INFINITY;
#pragma unroll
                for (int q2 = 0; q2 < 4; q2++) {
                    s4[q2] = bf16r(bf16r(s4[q2]) * 0.08838834764831845f);
                    mx = fmaxf(mx, s4[q2]);
                }
#pragma unroll
                for (int o = 1; o < 32; o <<= 1) mx = fmaxf(mx, __shfl_xor_sync(0xffffffffu, mx, o));
                float l = 0.f;
#pragma unroll
                for (int q2 = 0; q2 < 4; q2++) {
                    const bf16 pb = __float2bfloat16_rn(ex2((s4[q2] - mx) * LOG2E));
                    l += __bfloat162float(pb);
                    pw[(2 * t + (q2 >> 1)) * 16 + (q2 & 1) * 8 + g] = pb;
                }
                l = warp_sum(l);
                if (lane == 0) { stat[2 * w] = mx; stat[2 * w + 1] = l; }
            }
            __syncthreads();
            float m_cta = stat[0];
#pragma unroll
            for (int i = 1; i < 8; i++) m_cta = fmaxf(m_cta, stat[2 * i]);
            const float wfac = ex2((stat[2 * w] - m_cta) * LOG2E);
            if (tid == 0) {
                float l_cta = 0.f;
#pragma unroll
                for (int i = 0; i < 8; i++) l_cta += stat[2 * i + 1] * ex2((stat[2 * i] - m_cta) * LOG2E);
                asm volatile("st.relaxed.gpu.global.v4.u32 [%0], {%1,%2,%3,%4};" :: "l"(&g_ml[pass][b]),
                             "r"(__float_as_uint(m_cta)), "r"(__float_as_uint(l_cta)), "r"(epoch * 2 + pass + 1), "r"(0u) : "memory");
            }

            {
                const bf16* vbase = P.vc + kv_off + (4 * t) * DH + g * 8;
                float* ow = oscr + w * 128;
                constexpr int NK = 8 - VL;
                static_assert(NK % NVB == 0, "NVB");
                uint32_t vbuf[NVB][4][4];
#pragma unroll
                for (int u = 0; u < NVB - 1; u++)
#pragma unroll
                    for (int i = 0; i < 4; i++) ldg128_hint(vbuf[u][i], vbase + ((VL + u) * 16 + i) * DH, pol_norm);
                cp_async_wait_all();
                __syncwarp();
#pragma unroll 4
                for (int mt = 0; mt < 8; mt++) {
                    float cl[4] = {0.f, 0.f, 0.f, 0.f};
#pragma unroll
                    for (int kt = 0; kt < VL; kt++) {
                        const uint32_t b0 = *reinterpret_cast<const uint32_t*>(pw + kt * 16 + 2 * t);
                        const uint32_t b1 = *reinterpret_cast<const uint32_t*>(pw + kt * 16 + 2 * t + 8);
                        const int row = kt * 16 + (lane & 7) + ((lane >> 4) & 1) * 8;
                        uint32_t a[4];
                        ldmatrix4t(a, vland + row * 256 + (((2 * mt + ((lane >> 3) & 1)) ^ (lane & 7)) << 4));
                        mma16816(cl, a[0], a[1], a[2], a[3], b0, b1);
                    }
                    if (t == 0) { ow[mt * 16 + g] = cl[0] * wfac; ow[mt * 16 + 8 + g] = cl[2] * wfac; }
                }
                __syncwarp();
                if (w != 7) asm volatile("bar.arrive 1, 256;" ::: "memory");
                float oacc[4][4];
#pragma unroll
                for (int i = 0; i < 4; i++) { oacc[i][0] = oacc[i][1] = oacc[i][2] = oacc[i][3] = 0.f; }
#pragma unroll 1
                for (int hf = 0; hf < 2; hf++) {
#pragma unroll 1
                    for (int k0 = 0; k0 < NK; k0 += NVB) {
                        if (w == 7 && hf == 1 && k0 == 2) {
                            asm volatile("bar.sync 1, 256;" ::: "memory");
                            if (lane == 0) {
                                mbar_expect_tx(bar_stage, 81920);
#pragma unroll 1
                                for (int i = 0; i < 10; i++) tma_2d_hint(sbase + OFF_STAGE + i * 8192, &tm_wo, i * 64, h * DH + r * 64, bar_stage, pol_first);
                            }
                            __syncwarp();
                        }
#pragma unroll
                        for (int u = 0; u < NVB; u++) {
                            const int kt = k0 + u;
                            int nk = kt + NVB - 1, nh = hf;
                            if (nk >= NK) { nk -= NK; nh = hf + 1; }
                            if (nh < 2) {
                                const bf16* vp = vbase + (VL + nk) * 16 * DH + nh * 64;
#pragma unroll
                                for (int i = 0; i < 4; i++) ldg128_hint(vbuf[(u + NVB - 1) % NVB][i], vp + i * DH, pol_norm);
                            }
                            const uint2 pb = *reinterpret_cast<const uint2*>(pw + (VL + kt) * 16 + 4 * t);
#pragma unroll
                            for (int e = 0; e < 4; e++)
                                mma16816(oacc[e], __byte_perm(vbuf[u][0][e], vbuf[u][1][e], 0x5410), __byte_perm(vbuf[u][0][e], vbuf[u][1][e], 0x7632),
                                         __byte_perm(vbuf[u][2][e], vbuf[u][3][e], 0x5410), __byte_perm(vbuf[u][2][e], vbuf[u][3][e], 0x7632), pb.x, pb.y);
                        }
                    }
                    if (t == 0) {
                        float* o2 = ow + hf * 64 + g * 8;
                        float4 u0 = *reinterpret_cast<float4*>(o2), u1 = *reinterpret_cast<float4*>(o2 + 4);
                        u0.x += oacc[0][0] * wfac; u0.y += oacc[0][2] * wfac; u0.z += oacc[1][0] * wfac; u0.w += oacc[1][2] * wfac;
                        u1.x += oacc[2][0] * wfac; u1.y += oacc[2][2] * wfac; u1.z += oacc[3][0] * wfac; u1.w += oacc[3][2] * wfac;
                        *reinterpret_cast<float4*>(o2) = u0;
                        *reinterpret_cast<float4*>(o2 + 4) = u1;
                    }
#pragma unroll
                    for (int i = 0; i < 4; i++) { oacc[i][0] = oacc[i][1] = oacc[i][2] = oacc[i][3] = 0.f; }
                }
            }
            if (s == 0 && b < MLP_CTAS) {
#pragma unroll 1
                for (int idx = tid; idx < 2 * D_MODEL; idx += NT) {
                    const int row = idx >> 1, hf = idx & 1;
                    cp_async16_hint(sbase + OFF_W1 + row * 32 + hf * 16, P.w1 + (size_t)row * FF + b * MLP_UNITS + hf * 8, pol_first);
                    const int r2 = idx / 80, ch = idx - r2 * 80;
                    cp_async16_hint(sbase + OFF_W2 + r2 * 1280 + ((ch ^ (r2 & 7)) << 4), P.w2 + (size_t)(b * MLP_UNITS) * D_MODEL + idx * 8, pol_first);
                }
                cp_async_commit();
            }
            __syncthreads();
            if (tid < 128) {
                uint4 rec[4];
                {
                    unsigned it = 0;
                    const unsigned tag = epoch * 2 + pass + 1;
                    while (true) {
#pragma unroll
                        for (int i = 0; i < 4; i++)
                            asm volatile("ld.relaxed.gpu.global.v4.u32 {%0,%1,%2,%3}, [%4];"
                                         : "=r"(rec[i].x), "=r"(rec[i].y), "=r"(rec[i].z), "=r"(rec[i].w)
                                         : "l"(&g_ml[pass][(b & ~3) + i]) : "memory");
                        if (rec[0].z == tag && rec[1].z == tag && rec[2].z == tag && rec[3].z == tag) break;
                        if (++it > SPIN_LIMIT) __trap();
                    }
                }
                const float M = fmaxf(fmaxf(__uint_as_float(rec[0].x), __uint_as_float(rec[1].x)),
                                      fmaxf(__uint_as_float(rec[2].x), __uint_as_float(rec[3].x)));
                float L = 0.f;
#pragma unroll
                for (int i = 0; i < 4; i++) L += __uint_as_float(rec[i].y) * ex2((__uint_as_float(rec[i].x) - M) * LOG2E);
                const float scale = __fdividef(ex2((m_cta - M) * LOG2E), L);
                float sum = 0.f;
#pragma unroll
                for (int i = 0; i < 8; i++) sum += oscr[i * 128 + tid];
                if ((tid >> 6) == r) oex[r * 64 + (tid & 63)] = sum * scale;
                else st_async_b32(mapa(sbase + OFF_OEX + (r * 64 + (tid & 63)) * 4, r ^ 1), __float_as_uint(sum * scale), mapa(sbase + OFF_XBAR + 8, r ^ 1));
            }
            __syncthreads();
            if (tid < 64) {
                mbar_wait(sbase + OFF_XBAR + 8, pass);
                const float o = oex[tid] + oex[64 + tid];
                const bf16 hi = __float2bfloat16_rn(o);
                hs[32 + tid] = hi;
                hs[96 + tid] = __float2bfloat16_rn(o - __bfloat162float(hi));
            }
            mbar_wait(bar_stage, 1);
            __syncthreads();
            {
                float co[5][4];
#pragma unroll
                for (int i = 0; i < 5; i++) { co[i][0] = co[i][1] = co[i][2] = co[i][3] = 0.f; }
#pragma unroll 1
                for (int ks = 0; ks < 4; ks++) {
                    uint32_t b0 = 0, b1 = 0;
                    if (g < 2) {
                        b0 = *reinterpret_cast<const uint32_t*>(hs + 32 + g * 64 + ks * 16 + 2 * t);
                        b1 = *reinterpret_cast<const uint32_t*>(hs + 32 + g * 64 + ks * 16 + 2 * t + 8);
                    }
                    const int krow = ks * 16 + (lane & 7) + ((lane >> 4) & 1) * 8;
#pragma unroll
                    for (int i = 0; i < 5; i++) {
                        const int ch = 2 * (w * 5 + i) + ((lane >> 3) & 1);
                        uint32_t a[4];
                        ldmatrix4t(a, sbase + OFF_STAGE + (ch >> 3) * 8192 + krow * 128 + (((ch ^ lane) & 7) << 4));
                        mma16816(co[i], a[0], a[1], a[2], a[3], b0, b1);
                    }
                }
                if (t == 0) {
#pragma unroll
                    for (int i = 0; i < 5; i++) {
                        oscr[(w * 5 + i) * 16 + g] = co[i][0] + co[i][1];
                        oscr[(w * 5 + i) * 16 + 8 + g] = co[i][2] + co[i][3];
                    }
                }
                __syncwarp();
                if (lane < 20) {
                    const float4 v4 = *reinterpret_cast<const float4*>(oscr + w * 80 + lane * 4);
                    red_add_v4(acc + w * 80 + lane * 4, v4.x, v4.y, v4.z, v4.w);
                }
            }
            if (s == 0) {
                __syncthreads();
                if (tid == 224) {
                    mbar_expect_tx(bar_stage, 81920);
#pragma unroll 1
                    for (int i = 0; i < 5; i++) tma_2d_hint(sbase + OFF_STAGE + i * 16384, &tm_wq, h * DH + r * 64, i * 128, bar_stage, pol_first);
                }
            }
        } else if (b < MLP_CTAS) {
            {
                float ch4[4] = {0.f, 0.f, 0.f, 0.f};
#pragma unroll
                for (int k5 = 0; k5 < 5; k5++) {
                    const int ks = w * 5 + k5;
                    const uint32_t b0 = *reinterpret_cast<const uint32_t*>(xn + ks * 16 + 2 * t);
                    const uint32_t b1 = *reinterpret_cast<const uint32_t*>(xn + ks * 16 + 2 * t + 8);
                    const int krow = ks * 16 + (lane & 7) + ((lane >> 4) & 1) * 8;
                    uint32_t a[4];
                    ldmatrix4t(a, sbase + OFF_W1 + krow * 32 + ((lane >> 3) & 1) * 16);
                    mma16816(ch4, a[0], a[1], a[2], a[3], b0, b1);
                }
                if (t == 0) { oscr[w * 16 + g] = ch4[0]; oscr[w * 16 + 8 + g] = ch4[2]; }
            }
            __syncthreads();
            if (tid < 16) {
                float sum = 0.f;
#pragma unroll
                for (int i = 0; i < 8; i++) sum += oscr[i * 16 + tid];
                const float u = bf16r(bf16r(sum) + __bfloat162float(hs[16 + tid]));
                const float inner = 0.7978845608028654f * (u + 0.044715f * u * u * u);
                const float th = 1.0f - __fdividef(2.0f, ex2(inner * (2.0f * LOG2E)) + 1.0f);
                hs[tid] = __float2bfloat16_rn(0.5f * u * (1.0f + th));
            }
            __syncthreads();
            {
                const uint32_t b0 = *reinterpret_cast<const uint32_t*>(hs + 2 * t);
                const uint32_t b1 = *reinterpret_cast<const uint32_t*>(hs + 2 * t + 8);
                const int krow = (lane & 7) + ((lane >> 4) & 1) * 8;
#pragma unroll
                for (int i = 0; i < 5; i++) {
                    const int ch = 2 * (w * 5 + i) + ((lane >> 3) & 1);
                    uint32_t a[4];
                    float co[4] = {0.f, 0.f, 0.f, 0.f};
                    ldmatrix4t(a, sbase + OFF_W2 + krow * 1280 + ((ch ^ (lane & 7)) << 4));
                    mma16816(co, a[0], a[1], a[2], a[3], b0, b1);
                    if (t == 0) {
                        oscr[256 + (w * 5 + i) * 16 + g] = co[0];
                        oscr[256 + (w * 5 + i) * 16 + 8 + g] = co[2];
                    }
                }
                __syncwarp();
                if (lane < 20) {
                    const float4 v4 = *reinterpret_cast<const float4*>(oscr + 256 + w * 80 + lane * 4);
                    red_add_v4(acc + w * 80 + lane * 4, v4.x, v4.y, v4.z, v4.w);
                }
            }
        }
        if (s < 3) grid_barrier(base + NCTA * (s + 1));
    }
    __syncthreads();
    if (tid == 0) {
        __threadfence();
        const unsigned old = atomicAdd(&g_ctr, 1u);
        s_flag[1] = (old == base + 4 * NCTA - 1) ? 1u : 0u;
        __threadfence();
    }
    __syncthreads();
    if (s_flag[1]) {
        for (int e = tid; e < D_MODEL; e += NT) {
            float a = 0.f;
#pragma unroll
            for (int i = 0; i < NREP; i++) a += __ldcg(&g_acc[3][i][e]);
            const float o = bf16r(bf16r(a) + __bfloat162float(b2s[e]));
            P.out[e] = __float2bfloat16_rn(__bfloat162float(xs[e]) + o);
        }
    }
}

}

extern "C" void kernel_launch(void* const* d_in, const int* in_sizes, int n_in,
                              void* d_out, int out_size) {
    Params P;
    P.x = (const bf16*)d_in[0];
    P.kc = (const bf16*)d_in[1];
    P.vc = (const bf16*)d_in[2];
    P.wq = (const bf16*)d_in[3];
    P.wo = (const bf16*)d_in[4];
    P.w1 = (const bf16*)d_in[6];
    P.b1 = (const bf16*)d_in[7];
    P.w2 = (const bf16*)d_in[8];
    P.b2 = (const bf16*)d_in[9];
    P.out = (bf16*)d_out;

    cudaFuncSetAttribute(fused_kernel, cudaFuncAttributeMaxDynamicSharedMemorySize, SMEM_BYTES);

    typedef CUresult (*EncodeFn)(CUtensorMap*, CUtensorMapDataType, cuuint32_t, void*, const cuuint64_t*, const cuuint64_t*,
                                 const cuuint32_t*, const cuuint32_t*, CUtensorMapInterleave, CUtensorMapSwizzle,
                                 CUtensorMapL2promotion, CUtensorMapFloatOOBfill);
    void* fn = nullptr;
    cudaDriverEntryPointQueryResult qres;
    cudaGetDriverEntryPoint("cuTensorMapEncodeTiled", &fn, cudaEnableDefault, &qres);
    EncodeFn encode = (EncodeFn)fn;
    CUtensorMap tm_wq, tm_wo;
    {
        cuuint64_t dims[2] = {(cuuint64_t)(NHEAD * DH), (cuuint64_t)D_MODEL};
        cuuint64_t strides[1] = {(cuuint64_t)(NHEAD * DH * 2)};
        cuuint32_t box[2] = {64, 128};
        cuuint32_t es[2] = {1, 1};
        encode(&tm_wq, CU_TENSOR_MAP_DATA_TYPE_BFLOAT16, 2, (void*)P.wq, dims, strides, box, es, CU_TENSOR_MAP_INTERLEAVE_NONE,
               CU_TENSOR_MAP_SWIZZLE_128B, CU_TENSOR_MAP_L2_PROMOTION_NONE, CU_TENSOR_MAP_FLOAT_OOB_FILL_NONE);
    }
    {
        cuuint64_t dims[2] = {(cuuint64_t)D_MODEL, (cuuint64_t)(NHEAD * DH)};
        cuuint64_t strides[1] = {(cuuint64_t)(D_MODEL * 2)};
        cuuint32_t box[2] = {64, 64};
        cuuint32_t es[2] = {1, 1};
        encode(&tm_wo, CU_TENSOR_MAP_DATA_TYPE_BFLOAT16, 2, (void*)P.wo, dims, strides, box, es, CU_TENSOR_MAP_INTERLEAVE_NONE,
               CU_TENSOR_MAP_SWIZZLE_128B, CU_TENSOR_MAP_L2_PROMOTION_NONE, CU_TENSOR_MAP_FLOAT_OOB_FILL_NONE);
    }

    cudaLaunchConfig_t cfg = {};
    cfg.gridDim = dim3(NCTA);
    cfg.blockDim = dim3(NT);
    cfg.dynamicSmemBytes = SMEM_BYTES;
    cfg.stream = cudaStreamPerThread;
    cudaLaunchAttribute at[2];
    at[0].id = cudaLaunchAttributeClusterDimension;
    at[0].val.clusterDim.x = 2; at[0].val.clusterDim.y = 1; at[0].val.clusterDim.z = 1;
    at[1].id = cudaLaunchAttributeCooperative;
    at[1].val.cooperative = 1;
    cfg.attrs = at;
    cfg.numAttrs = 2;
    cudaLaunchKernelEx(&cfg, fused_kernel, P, tm_wq, tm_wo);
}
```

```cpp
#include <cuda_runtime.h>
#include <cuda.h>
#include <cuda_bf16.h>
#include <stdint.h>

typedef __nv_bfloat16 bf16;

namespace {

constexpr int D_MODEL = 640;
constexpr int NHEAD = 32;
constexpr int SEQ = 4096;
constexpr int DH = 128;
constexpr int FF = 1728;
constexpr int NCTA = 128;
constexpr int NT = 256;
constexpr int KREG_TILES = 5;
constexpr int KSM_TILES = 3;
constexpr int MLP_UNITS = 16;
constexpr int MLP_CTAS = FF / MLP_UNITS;

constexpr int OFF_STAGE = 0;
constexpr int OFF_W2 = 81920;
constexpr int OFF_W1 = OFF_W2 + 20480;
constexpr int OFF_K = OFF_W1 + 20480;
constexpr int OFF_XS = OFF_K + 98304;
constexpr int OFF_XN = OFF_XS + 1280;
constexpr int OFF_O = OFF_XN + 1280;
constexpr int OFF_P = OFF_O + 4096;
constexpr int OFF_Q = OFF_P + 2048;
constexpr int OFF_OEX = OFF_Q + 256;
constexpr int OFF_STAT = OFF_OEX + 512;
constexpr int OFF_RED = OFF_STAT + 80;
constexpr int OFF_HS = OFF_RED + 96;
constexpr int OFF_B2 = OFF_HS + 320;
constexpr int OFF_XBAR = OFF_B2 + 1280;
constexpr int SMEM_BYTES = OFF_XBAR + 16;

static_assert(SMEM_BYTES <= 232448, "smem");
constexpr int NREP = 8;
constexpr int VL = 2;
constexpr int NVB = 2;
constexpr unsigned SPIN_LIMIT = 1u << 24;

__device__ unsigned int g_ctr;
__device__ float g_acc[4][NREP][D_MODEL];
__device__ uint4 g_ml[2][NCTA];

struct Params {
    const bf16* x; const bf16* kc; const bf16* vc; const bf16* wq; const bf16* wo;
    const bf16* w1; const bf16* b1; const bf16* w2; const bf16* b2; bf16* out;
};

__device__ __forceinline__ float bf16r(float x) { return __bfloat162float(__float2bfloat16_rn(x)); }
__device__ __forceinline__ float bflo(uint32_t u) { return __uint_as_float(u << 16); }
__device__ __forceinline__ float bfhi(uint32_t u) { return __uint_as_float(u & 0xffff0000u); }

__device__ __forceinline__ uint32_t smem_u32(const void* p) { return (uint32_t)__cvta_generic_to_shared(p); }

__device__ __forceinline__ void mbar_init(uint32_t bar, uint32_t cnt) {
    asm volatile("mbarrier.init.shared::cta.b64 [%0], %1;" :: "r"(bar), "r"(cnt) : "memory");
}
__device__ __forceinline__ void mbar_expect_tx(uint32_t bar, uint32_t bytes) {
    asm volatile("mbarrier.arrive.expect_tx.shared::cta.b64 _, [%0], %1;" :: "r"(bar), "r"(bytes) : "memory");
}
__device__ __forceinline__ void mbar_wait(uint32_t bar, uint32_t parity) {
    unsigned it = 0;
    while (true) {
        uint32_t ok;
        asm volatile("{\n\t.reg .pred p;\n\tmbarrier.try_wait.parity.shared::cta.b64 p, [%1], %2;\n\tselp.u32 %0, 1, 0, p;\n\t}"
                     : "=r"(ok) : "r"(bar), "r"(parity) : "memory");
        if (ok) break;
        if (++it > SPIN_LIMIT) __trap();
    }
}
__device__ __forceinline__ void tma_2d_hint(uint32_t dst, const CUtensorMap* tm, int c0, int c1, uint32_t bar, uint64_t pol) {
    asm volatile("cp.async.bulk.tensor.2d.shared::cluster.global.mbarrier::complete_tx::bytes.L2::cache_hint [%0], [%1, {%3, %4}], [%2], %5;"
                 :: "r"(dst), "l"(tm), "r"(bar), "r"(c0), "r"(c1), "l"(pol) : "memory");
}
__device__ __forceinline__ void bulk_prefetch_l2(const void* src, uint32_t bytes) {
    asm volatile("cp.async.bulk.prefetch.L2.global [%0], %1;" :: "l"(src), "r"(bytes) : "memory");
}
__device__ __forceinline__ float ex2(float x) { float y; asm("ex2.approx.ftz.f32 %0, %1;" : "=f"(y) : "f"(x)); return y; }
__device__ __forceinline__ void cp_async16_hint(uint32_t dst, const void* src, uint64_t pol) {
    asm volatile("cp.async.cg.shared.global.L2::cache_hint [%0], [%1], 16, %2;" :: "r"(dst), "l"(src), "l"(pol) : "memory");
}
__device__ __forceinline__ void cp_async_wait_all() { asm volatile("cp.async.wait_all;" ::: "memory"); }
__device__ __forceinline__ void cp_async_commit() { asm volatile("cp.async.commit_group;" ::: "memory"); }
template <int N> __device__ __forceinline__ void cp_async_wait_group() { asm volatile("cp.async.wait_group %0;" :: "n"(N) : "memory"); }

__device__ __forceinline__ void ldg128_hint(uint32_t (&r)[4], const void* p, uint64_t pol) {
    asm volatile("ld.global.nc.L1::no_allocate.L2::cache_hint.v4.u32 {%0,%1,%2,%3}, [%4], %5;"
                 : "=r"(r[0]), "=r"(r[1]), "=r"(r[2]), "=r"(r[3]) : "l"(p), "l"(pol));
}
__device__ __forceinline__ void mma16816(float (&c)[4], uint32_t a0, uint32_t a1, uint32_t a2, uint32_t a3,
                                         uint32_t b0, uint32_t b1) {
    asm volatile("mma.sync.aligned.m16n8k16.row.col.f32.bf16.bf16.f32 {%0,%1,%2,%3}, {%4,%5,%6,%7}, {%8,%9}, {%0,%1,%2,%3};"
                 : "+f"(c[0]), "+f"(c[1]), "+f"(c[2]), "+f"(c[3])
                 : "r"(a0), "r"(a1), "r"(a2), "r"(a3), "r"(b0), "r"(b1));
}
__device__ __forceinline__ void ldmatrix4(uint32_t (&r)[4], uint32_t addr) {
    asm volatile("ldmatrix.sync.aligned.m8n8.x4.shared.b16 {%0,%1,%2,%3}, [%4];"
                 : "=r"(r[0]), "=r"(r[1]), "=r"(r[2]), "=r"(r[3]) : "r"(addr) : "memory");
}
__device__ __forceinline__ void red_add_v4(float* p, float a, float b, float c, float d) {
    asm volatile("red.global.add.v4.f32 [%0], {%1,%2,%3,%4};" :: "l"(p), "f"(a), "f"(b), "f"(c), "f"(d) : "memory");
}
__device__ __forceinline__ unsigned ld_acquire(const unsigned* p) {
    unsigned v; asm volatile("ld.acquire.gpu.global.u32 %0, [%1];" : "=r"(v) : "l"(p) : "memory"); return v;
}
__device__ __forceinline__ uint32_t mapa(uint32_t addr, uint32_t rank) {
    uint32_t r; asm volatile("mapa.shared::cluster.u32 %0, %1, %2;" : "=r"(r) : "r"(addr), "r"(rank)); return r;
}
__device__ __forceinline__ void st_async_b32(uint32_t addr, uint32_t v, uint32_t bar) {
    asm volatile("st.async.weak.shared::cluster.mbarrier::complete_tx::bytes.b32 [%0], %1, [%2];" :: "r"(addr), "r"(v), "r"(bar) : "memory");
}
__device__ __forceinline__ float warp_sum(float v) {
#pragma unroll
    for (int o = 16; o > 0; o >>= 1) v += __shfl_xor_sync(0xffffffffu, v, o);
    return v;
}

__device__ __forceinline__ void grid_barrier(unsigned target) {
    __syncthreads();
    if (threadIdx.x == 0) {
        __threadfence();
        atomicAdd(&g_ctr, 1u);
        unsigned it = 0;
        while ((int)(ld_acquire(&g_ctr) - target) < 0) { if (++it > SPIN_LIMIT) __trap(); }
    }
    __syncthreads();
}

constexpr float LOG2E = 1.4426950408889634f;

__device__ __forceinline__ void ldmatrix4t(uint32_t (&r)[4], uint32_t addr) {
    asm volatile("ldmatrix.sync.aligned.m8n8.x4.trans.shared.b16 {%0,%1,%2,%3}, [%4];"
                 : "=r"(r[0]), "=r"(r[1]), "=r"(r[2]), "=r"(r[3]) : "r"(addr) : "memory");
}
__device__ __forceinline__ uint32_t pack_bf16(float lo, float hi) {
    uint32_t r; asm("cvt.rn.bf16x2.f32 %0, %1, %2;" : "=r"(r) : "f"(hi), "f"(lo)); return r;
}

__global__ void __launch_bounds__(NT, 1) fused_kernel(const Params P, const __grid_constant__ CUtensorMap tm_wq,
                                                        const __grid_constant__ CUtensorMap tm_wo) {
    extern __shared__ __align__(1024) unsigned char sm[];
    const int tid = threadIdx.x, lane = tid & 31, w = tid >> 5;
    const int g = lane >> 2, t = lane & 3;
    const int b = blockIdx.x, h = b >> 2, c = b & 3, r = b & 1;
    const uint32_t sbase = smem_u32(sm);
    bf16* xs = reinterpret_cast<bf16*>(sm + OFF_XS);
    bf16* xn = reinterpret_cast<bf16*>(sm + OFF_XN);
    bf16* b2s = reinterpret_cast<bf16*>(sm + OFF_B2);
    float* oscr = reinterpret_cast<float*>(sm + OFF_O);
    bf16* qs = reinterpret_cast<bf16*>(sm + OFF_Q);
    float* oex = reinterpret_cast<float*>(sm + OFF_OEX);
    float* stat = reinterpret_cast<float*>(sm + OFF_STAT);
    float* red = reinterpret_cast<float*>(sm + OFF_RED);
    bf16* hs = reinterpret_cast<bf16*>(sm + OFF_HS);
    volatile unsigned* s_flag = reinterpret_cast<volatile unsigned*>(sm + OFF_STAT + 64);
    const uint32_t bar_stage = sbase + OFF_STAT + 72;
    if (tid < D_MODEL / 8) *reinterpret_cast<uint4*>(xs + tid * 8) = __ldg(reinterpret_cast<const uint4*>(P.x) + tid);
    else if (tid < D_MODEL / 4) *reinterpret_cast<uint4*>(b2s + (tid - 80) * 8) = __ldg(reinterpret_cast<const uint4*>(P.b2) + (tid - 80));
    else if (tid < 162) { if (b < MLP_CTAS) *reinterpret_cast<uint4*>(hs + 16 + (tid - 160) * 8) = __ldg(reinterpret_cast<const uint4*>(P.b1 + b * MLP_UNITS) + (tid - 160)); }
    else if (tid == 192) s_flag[0] = ld_acquire(&g_ctr) >> 9;
    uint64_t pol_first;
    asm volatile("createpolicy.fractional.L2::evict_first.b64 %0, 1.0;" : "=l"(pol_first));
    uint64_t pol_norm;
    asm volatile("createpolicy.fractional.L2::evict_normal.b64 %0, 1.0;" : "=l"(pol_norm));

    const size_t kv_off = (size_t)(h * SEQ + c * 1024 + w * 128) * DH;
    if (tid == 224) {
        mbar_init(bar_stage, 1);
        mbar_init(sbase + OFF_XBAR, 1);
        mbar_init(sbase + OFF_XBAR + 8, 1);
        asm volatile("fence.mbarrier_init.release.cluster;" ::: "memory");
        asm volatile("fence.proxy.async.shared::cta;" ::: "memory");
        mbar_expect_tx(bar_stage, 81920);
#pragma unroll
        for (int i = 0; i < 5; i++) tma_2d_hint(sbase + OFF_STAGE + i * 16384, &tm_wq, h * DH + r * 64, i * 128, bar_stage, pol_first);
    }
    const uint32_t kb = sbase + OFF_K + w * (KSM_TILES * 16 * 256);
    if (b == 1) for (int e = tid; e < 3 * NREP * D_MODEL; e += NT) (&g_acc[1][0][0])[e] = 0.f;
    uint32_t kreg[KREG_TILES][2][4][4];
    __syncthreads();
    asm volatile("barrier.cluster.arrive.relaxed.aligned;" ::: "memory");
    const unsigned epoch = s_flag[0];
    const unsigned base = epoch << 9;

#pragma unroll 1
    for (int s = 0; s < 4; s++) {
        {
            float v[4] = {0.f, 0.f, 0.f, 0.f};
            if (tid < D_MODEL / 4) {
                const uint2 xr = *reinterpret_cast<const uint2*>(xs + tid * 4);
                v[0] = bflo(xr.x); v[1] = bfhi(xr.x); v[2] = bflo(xr.y); v[3] = bfhi(xr.y);
                if (s != 0) {
                    float4 a = __ldcg(reinterpret_cast<const float4*>(&g_acc[s - 1][0][0]) + tid);
#pragma unroll
                    for (int i = 1; i < NREP; i++) {
                        const float4 a2 = __ldcg(reinterpret_cast<const float4*>(&g_acc[s - 1][i][0]) + tid);
                        a.x += a2.x; a.y += a2.y; a.z += a2.z; a.w += a2.w;
                    }
                    a.x = bf16r(a.x); a.y = bf16r(a.y); a.z = bf16r(a.z); a.w = bf16r(a.w);
                    if (s == 2) {
                        const uint2 br = *reinterpret_cast<const uint2*>(b2s + tid * 4);
                        a.x = bf16r(a.x + bflo(br.x)); a.y = bf16r(a.y + bfhi(br.x));
                        a.z = bf16r(a.z + bflo(br.y)); a.w = bf16r(a.w + bfhi(br.y));
                    }
                    v[0] = bf16r(v[0] + a.x); v[1] = bf16r(v[1] + a.y); v[2] = bf16r(v[2] + a.z); v[3] = bf16r(v[3] + a.w);
                    *reinterpret_cast<uint2*>(xs + tid * 4) = make_uint2(pack_bf16(v[0], v[1]), pack_bf16(v[2], v[3]));
                }
            }
            if (s == 2 && b == 0) {
                for (int e = tid; e < NREP * D_MODEL; e += NT) (&g_acc[0][0][0])[e] = 0.f;
            }
#pragma unroll 1
            for (int rep = 0; rep <= (s & 1); rep++) {
                float mean = 0.25f * ((v[0] + v[1]) + (v[2] + v[3]));
                float m2 = (v[0] - mean) * (v[0] - mean) + (v[1] - mean) * (v[1] - mean) +
                           (v[2] - mean) * (v[2] - mean) + (v[3] - mean) * (v[3] - mean);
                float hn = 2.f;
#pragma unroll
                for (int o = 1; o < 32; o <<= 1) {
                    const float mo = __shfl_xor_sync(0xffffffffu, mean, o);
                    const float qo = __shfl_xor_sync(0xffffffffu, m2, o);
                    const float d = mo - mean;
                    m2 = m2 + qo + d * d * hn;
                    mean = 0.5f * (mean + mo);
                    hn *= 2.f;
                }
                float* rd = red + rep * 12;
                if (lane == 0 && w < 5) { rd[2 * w] = mean; rd[2 * w + 1] = m2; }
                __syncthreads();
                float gm = 0.f, gq = 0.f;
#pragma unroll
                for (int i = 0; i < 5; i++) { gm += rd[2 * i]; gq += rd[2 * i + 1]; }
                gm *= 0.2f;
#pragma unroll
                for (int i = 0; i < 5; i++) { const float d = rd[2 * i] - gm; gq += 128.f * d * d; }
                const float mb = bf16r(gm);
                const float den = bf16r(sqrtf(bf16r(bf16r(gq * (1.0f / D_MODEL)) + 1e-5f)));
#pragma unroll
                for (int i = 0; i < 4; i++) v[i] = bf16r(__fdividef(bf16r(v[i] - mb), den));
            }
            if (tid < D_MODEL / 4)
                *reinterpret_cast<uint2*>(xn + tid * 4) = make_uint2(pack_bf16(v[0], v[1]), pack_bf16(v[2], v[3]));
        }
        if (s == 1) cp_async_wait_all();
        __syncthreads();
        float* acc = &g_acc[s][b & (NREP - 1)][0];

        if (!(s & 1)) {
            const int pass = s >> 1;
            mbar_wait(bar_stage, 0);
            {
                float cq[4][4];
#pragma unroll
                for (int i = 0; i < 4; i++) { cq[i][0] = cq[i][1] = cq[i][2] = cq[i][3] = 0.f; }
#pragma unroll
                for (int k5 = 0; k5 < 5; k5++) {
                    const int ks = w * 5 + k5;
                    const uint32_t b0 = *reinterpret_cast<const uint32_t*>(xn + ks * 16 + 2 * t);
                    const uint32_t b1 = *reinterpret_cast<const uint32_t*>(xn + ks * 16 + 2 * t + 8);
                    const int krow = ks * 16 + (lane & 7) + ((lane >> 4) & 1) * 8;
#pragma unroll
                    for (int mt = 0; mt < 4; mt++) {
                        uint32_t a[4];
                        ldmatrix4t(a, sbase + OFF_STAGE + krow * 128 + (((2 * mt + ((lane >> 3) & 1)) ^ (lane & 7)) << 4));
                        mma16816(cq[mt], a[0], a[1], a[2], a[3], b0, b1);
                    }
                }
                if (t == 0) {
#pragma unroll
                    for (int mt = 0; mt < 4; mt++) { oscr[w * 64 + mt * 16 + g] = cq[mt][0]; oscr[w * 64 + mt * 16 + 8 + g] = cq[mt][2]; }
                }
            }
            __syncthreads();
            if (s == 0) asm volatile("barrier.cluster.wait.aligned;" ::: "memory");
            if (tid < 32) {
                float s0 = 0.f, s1 = 0.f;
#pragma unroll
                for (int i = 0; i < 8; i++) { const float2 v2 = *reinterpret_cast<const float2*>(oscr + i * 64 + 2 * tid); s0 += v2.x; s1 += v2.y; }
                const uint32_t qp = pack_bf16(s0, s1);
                *reinterpret_cast<uint32_t*>(qs + r * 64 + 2 * tid) = qp;
                st_async_b32(mapa(sbase + OFF_Q + (r * 64 + 2 * tid) * 2, r ^ 1), qp, mapa(sbase + OFF_XBAR, r ^ 1));
                if (tid == 0) { mbar_expect_tx(sbase + OFF_XBAR, 128); mbar_expect_tx(sbase + OFF_XBAR + 8, 256); }
            }
            if (s == 0) {
                const bf16* kq = P.kc + kv_off + KREG_TILES * 16 * DH;
#pragma unroll 1
                for (int it = 0; it < KSM_TILES * 8; it++) {
                    const int idx = it * 32 + lane;
                    const int row = idx >> 4, ch = idx & 15;
                    cp_async16_hint(kb + row * 256 + ((ch ^ (row & 7)) << 4), kq + row * DH + ch * 8, pol_first);
                }
                cp_async_commit();
            }
            const uint32_t vland = sbase + OFF_STAGE + w * (VL * 4096);
#pragma unroll 1
            for (int it = 0; it < VL * 8; it++) {
                const int idx = it * 32 + lane;
                const int row = idx >> 4, ch = idx & 15;
                cp_async16_hint(vland + row * 256 + ((ch ^ (row & 7)) << 4), P.vc + kv_off + row * DH + ch * 8, pol_first);
            }
            cp_async_commit();
            if (s == 0) {
                const bf16* kp = P.kc + kv_off + (g * DH + t * 8);
#pragma unroll
                for (int i = 0; i < KREG_TILES; i++)
#pragma unroll
                    for (int hh = 0; hh < 2; hh++)
#pragma unroll
                        for (int j = 0; j < 4; j++)
                            ldg128_hint(kreg[i][hh][j], kp + (i * 16 + hh * 8) * DH + j * 32, pol_first);
            }
            __syncthreads();
            mbar_wait(sbase + OFF_XBAR, pass);

            float sc[8][2];
            {
                float cacc[KREG_TILES][4];
#pragma unroll
                for (int i = 0; i < KREG_TILES; i++) { cacc[i][0] = cacc[i][1] = cacc[i][2] = cacc[i][3] = 0.f; }
#pragma unroll
                for (int j = 0; j < 4; j++) {
                    const uint4 qv = *reinterpret_cast<const uint4*>(qs + j * 32 + t * 8);
#pragma unroll
                    for (int i = 0; i < KREG_TILES; i++) {
                        mma16816(cacc[i], kreg[i][0][j][0], kreg[i][1][j][0], kreg[i][0][j][1], kreg[i][1][j][1], qv.x, qv.y);
                        mma16816(cacc[i], kreg[i][0][j][2], kreg[i][1][j][2], kreg[i][0][j][3], kreg[i][1][j][3], qv.z, qv.w);
                    }
                }
#pragma unroll
                for (int i = 0; i < KREG_TILES; i++) { sc[i][0] = cacc[i][0]; sc[i][1] = cacc[i][2]; }
            }
            {
                if (s == 0) {
                    if (lane == 0) bulk_prefetch_l2(P.vc + kv_off + VL * 16 * DH, (8 - VL) * 4096);
                    cp_async_wait_group<1>();
                    __syncwarp();
                }
                float cacc[KSM_TILES][4];
#pragma unroll
                for (int tt = 0; tt < KSM_TILES; tt++) { cacc[tt][0] = cacc[tt][1] = cacc[tt][2] = cacc[tt][3] = 0.f; }
                const int row0 = (lane & 7) + ((lane >> 3) & 1) * 8;
#pragma unroll 4
                for (int ks = 0; ks < 8; ks++) {
                    const uint32_t b0 = *reinterpret_cast<const uint32_t*>(qs + ks * 16 + 2 * t);
                    const uint32_t b1 = *reinterpret_cast<const uint32_t*>(qs + ks * 16 + 2 * t + 8);
                    const int ch = 2 * ks + (lane >> 4);
                    const uint32_t ad = kb + row0 * 256 + ((ch ^ (lane & 7)) << 4);
#pragma unroll
                    for (int tt = 0; tt < KSM_TILES; tt++) {
                        uint32_t a[4];
                        ldmatrix4(a, ad + tt * 4096);
                        mma16816(cacc[tt], a[0], a[1], a[2], a[3], b0, b1);
                    }
                }
#pragma unroll
                for (int tt = 0; tt < KSM_TILES; tt++) { sc[KREG_TILES + tt][0] = cacc[tt][0]; sc[KREG_TILES + tt][1] = cacc[tt][2]; }
            }
            bf16* pw = reinterpret_cast<bf16*>(sm + OFF_P + w * 256);
            {
                float s4[4];
#pragma unroll
                for (int q2 = 0; q2 < 4; q2++) {
                    const int i = q2 >> 1, k2 = q2 & 1;
                    const float v01 = (t & 1) ? sc[2 + i][k2] : sc[i][k2];
                    const float v23 = (t & 1) ? sc[6 + i][k2] : sc[4 + i][k2];
                    s4[q2] = (t & 2) ? v23 : v01;
                }
                float mx = -INFINITY;
#pragma unroll
                for (int q2 = 0; q2 < 4; q2++) {
                    s4[q2] = bf16r(bf16r(s4[q2]) * 0.08838834764831845f);
                    mx = fmaxf(mx, s4[q2]);
                }
#pragma unroll
                for (int o = 1; o < 32; o <<= 1) mx = fmaxf(mx, __shfl_xor_sync(0xffffffffu, mx, o));
                float l = 0.f;
#pragma unroll
                for (int q2 = 0; q2 < 4; q2++) {
                    const bf16 pb = __float2bfloat16_rn(ex2((s4[q2] - mx) * LOG2E));
                    l += __bfloat162float(pb);
                    pw[(2 * t + (q2 >> 1)) * 16 + (q2 & 1) * 8 + g] = pb;
                }
                l = warp_sum(l);
                if (lane == 0) { stat[2 * w] = mx; stat[2 * w + 1] = l; }
            }
            __syncthreads();
            float m_cta = stat[0];
#pragma unroll
            for (int i = 1; i < 8; i++) m_cta = fmaxf(m_cta, stat[2 * i]);
            const float wfac = ex2((stat[2 * w] - m_cta) * LOG2E);
            if (tid == 0) {
                float l_cta = 0.f;
#pragma unroll
                for (int i = 0; i < 8; i++) l_cta += stat[2 * i + 1] * ex2((stat[2 * i] - m_cta) * LOG2E);
                asm volatile("st.relaxed.gpu.global.v4.u32 [%0], {%1,%2,%3,%4};" :: "l"(&g_ml[pass][b]),
                             "r"(__float_as_uint(m_cta)), "r"(__float_as_uint(l_cta)), "r"(epoch * 2 + pass + 1), "r"(0u) : "memory");
            }

            {
                const bf16* vbase = P.vc + kv_off + (4 * t) * DH + g * 8;
                float* ow = oscr + w * 128;
                constexpr int NK = 8 - VL;
                static_assert(NK % NVB == 0, "NVB");
                uint32_t vbuf[NVB][4][4];
#pragma unroll
                for (int u = 0; u < NVB - 1; u++)
#pragma unroll
                    for (int i = 0; i < 4; i++) ldg128_hint(vbuf[u][i], vbase + ((VL + u) * 16 + i) * DH, pol_norm);
                cp_async_wait_all();
                __syncwarp();
#pragma unroll 4
                for (int mt = 0; mt < 8; mt++) {
                    float cl[4] = {0.f, 0.f, 0.f, 0.f};
#pragma unroll
                    for (int kt = 0; kt < VL; kt++) {
                        const uint32_t b0 = *reinterpret_cast<const uint32_t*>(pw + kt * 16 + 2 * t);
                        const uint32_t b1 = *reinterpret_cast<const uint32_t*>(pw + kt * 16 + 2 * t + 8);
                        const int row = kt * 16 + (lane & 7) + ((lane >> 4) & 1) * 8;
                        uint32_t a[4];
                        ldmatrix4t(a, vland + row * 256 + (((2 * mt + ((lane >> 3) & 1)) ^ (lane & 7)) << 4));
                        mma16816(cl, a[0], a[1], a[2], a[3], b0, b1);
                    }
                    if (t == 0) { ow[mt * 16 + g] = cl[0] * wfac; ow[mt * 16 + 8 + g] = cl[2] * wfac; }
                }
                __syncwarp();
                if (w != 7) asm volatile("bar.arrive 1, 256;" ::: "memory");
                float oacc[4][4];
#pragma unroll
                for (int i = 0; i < 4; i++) { oacc[i][0] = oacc[i][1] = oacc[i][2] = oacc[i][3] = 0.f; }
#pragma unroll 1
                for (int hf = 0; hf < 2; hf++) {
#pragma unroll 1
                    for (int k0 = 0; k0 < NK; k0 += NVB) {
                        if (w == 7 && hf == 1 && k0 == 2) {
                            asm volatile("bar.sync 1, 256;" ::: "memory");
                            if (lane == 0) {
                                mbar_expect_tx(bar_stage, 81920);
#pragma unroll 1
                                for (int i = 0; i < 10; i++) tma_2d_hint(sbase + OFF_STAGE + i * 8192, &tm_wo, i * 64, h * DH + r * 64, bar_stage, pol_first);
                            }
                            __syncwarp();
                        }
#pragma unroll
                        for (int u = 0; u < NVB; u++) {
                            const int kt = k0 + u;
                            int nk = kt + NVB - 1, nh = hf;
                            if (nk >= NK) { nk -= NK; nh = hf + 1; }
                            if (nh < 2) {
                                const bf16* vp = vbase + (VL + nk) * 16 * DH + nh * 64;
#pragma unroll
                                for (int i = 0; i < 4; i++) ldg128_hint(vbuf[(u + NVB - 1) % NVB][i], vp + i * DH, pol_norm);
                            }
                            const uint2 pb = *reinterpret_cast<const uint2*>(pw + (VL + kt) * 16 + 4 * t);
#pragma unroll
                            for (int e = 0; e < 4; e++)
                                mma16816(oacc[e], __byte_perm(vbuf[u][0][e], vbuf[u][1][e], 0x5410), __byte_perm(vbuf[u][0][e], vbuf[u][1][e], 0x7632),
                                         __byte_perm(vbuf[u][2][e], vbuf[u][3][e], 0x5410), __byte_perm(vbuf[u][2][e], vbuf[u][3][e], 0x7632), pb.x, pb.y);
                        }
                    }
                    if (t == 0) {
                        float* o2 = ow + hf * 64 + g * 8;
                        float4 u0 = *reinterpret_cast<float4*>(o2), u1 = *reinterpret_cast<float4*>(o2 + 4);
                        u0.x += oacc[0][0] * wfac; u0.y += oacc[0][2] * wfac; u0.z += oacc[1][0] * wfac; u0.w += oacc[1][2] * wfac;
                        u1.x += oacc[2][0] * wfac; u1.y += oacc[2][2] * wfac; u1.z += oacc[3][0] * wfac; u1.w += oacc[3][2] * wfac;
                        *reinterpret_cast<float4*>(o2) = u0;
                        *reinterpret_cast<float4*>(o2 + 4) = u1;
                    }
#pragma unroll
                    for (int i = 0; i < 4; i++) { oacc[i][0] = oacc[i][1] = oacc[i][2] = oacc[i][3] = 0.f; }
                }
            }
            if (s == 0 && b < MLP_CTAS) {
#pragma unroll 1
                for (int idx = tid; idx < 2 * D_MODEL; idx += NT) {
                    const int row = idx >> 1, hf = idx & 1;
                    cp_async16_hint(sbase + OFF_W1 + row * 32 + hf * 16, P.w1 + (size_t)row * FF + b * MLP_UNITS + hf * 8, pol_first);
                    const int r2 = idx / 80, ch = idx - r2 * 80;
                    cp_async16_hint(sbase + OFF_W2 + r2 * 1280 + ((ch ^ (r2 & 7)) << 4), P.w2 + (size_t)(b * MLP_UNITS) * D_MODEL + idx * 8, pol_first);
                }
                cp_async_commit();
            }
            __syncthreads();
            if (tid < 128) {
                uint4 rec[4];
                {
                    unsigned it = 0;
                    const unsigned tag = epoch * 2 + pass + 1;
                    while (true) {
#pragma unroll
                        for (int i = 0; i < 4; i++)
                            asm volatile("ld.relaxed.gpu.global.v4.u32 {%0,%1,%2,%3}, [%4];"
                                         : "=r"(rec[i].x), "=r"(rec[i].y), "=r"(rec[i].z), "=r"(rec[i].w)
                                         : "l"(&g_ml[pass][(b & ~3) + i]) : "memory");
                        if (rec[0].z == tag && rec[1].z == tag && rec[2].z == tag && rec[3].z == tag) break;
                        if (++it > SPIN_LIMIT) __trap();
                    }
                }
                const float M = fmaxf(fmaxf(__uint_as_float(rec[0].x), __uint_as_float(rec[1].x)),
                                      fmaxf(__uint_as_float(rec[2].x), __uint_as_float(rec[3].x)));
                float L = 0.f;
#pragma unroll
                for (int i = 0; i < 4; i++) L += __uint_as_float(rec[i].y) * ex2((__uint_as_float(rec[i].x) - M) * LOG2E);
                const float scale = __fdividef(ex2((m_cta - M) * LOG2E), L);
                float sum = 0.f;
#pragma unroll
                for (int i = 0; i < 8; i++) sum += oscr[i * 128 + tid];
                if ((tid >> 6) == r) oex[r * 64 + (tid & 63)] = sum * scale;
                else st_async_b32(mapa(sbase + OFF_OEX + (r * 64 + (tid & 63)) * 4, r ^ 1), __float_as_uint(sum * scale), mapa(sbase + OFF_XBAR + 8, r ^ 1));
            }
            __syncthreads();
            if (tid < 64) {
                mbar_wait(sbase + OFF_XBAR + 8, pass);
                const float o = oex[tid] + oex[64 + tid];
                const bf16 hi = __float2bfloat16_rn(o);
                hs[32 + tid] = hi;
                hs[96 + tid] = __float2bfloat16_rn(o - __bfloat162float(hi));
            }
            mbar_wait(bar_stage, 1);
            __syncthreads();
            {
                float co[5][4];
#pragma unroll
                for (int i = 0; i < 5; i++) { co[i][0] = co[i][1] = co[i][2] = co[i][3] = 0.f; }
#pragma unroll 1
                for (int ks = 0; ks < 4; ks++) {
                    uint32_t b0 = 0, b1 = 0;
                    if (g < 2) {
                        b0 = *reinterpret_cast<const uint32_t*>(hs + 32 + g * 64 + ks * 16 + 2 * t);
                        b1 = *reinterpret_cast<const uint32_t*>(hs + 32 + g * 64 + ks * 16 + 2 * t + 8);
                    }
                    const int krow = ks * 16 + (lane & 7) + ((lane >> 4) & 1) * 8;
#pragma unroll
                    for (int i = 0; i < 5; i++) {
                        const int ch = 2 * (w * 5 + i) + ((lane >> 3) & 1);
                        uint32_t a[4];
                        ldmatrix4t(a, sbase + OFF_STAGE + (ch >> 3) * 8192 + krow * 128 + (((ch ^ lane) & 7) << 4));
                        mma16816(co[i], a[0], a[1], a[2], a[3], b0, b1);
                    }
                }
                if (t == 0) {
#pragma unroll
                    for (int i = 0; i < 5; i++) {
                        oscr[(w * 5 + i) * 16 + g] = co[i][0] + co[i][1];
                        oscr[(w * 5 + i) * 16 + 8 + g] = co[i][2] + co[i][3];
                    }
                }
                __syncwarp();
                if (lane < 20) {
                    const float4 v4 = *reinterpret_cast<const float4*>(oscr + w * 80 + lane * 4);
                    red_add_v4(acc + w * 80 + lane * 4, v4.x, v4.y, v4.z, v4.w);
                }
            }
            if (s == 0) {
                __syncthreads();
                if (tid == 224) {
                    mbar_expect_tx(bar_stage, 81920);
#pragma unroll 1
                    for (int i = 0; i < 5; i++) tma_2d_hint(sbase + OFF_STAGE + i * 16384, &tm_wq, h * DH + r * 64, i * 128, bar_stage, pol_first);
                }
            }
        } else if (b < MLP_CTAS) {
            {
                float ch4[4] = {0.f, 0.f, 0.f, 0.f};
#pragma unroll
                for (int k5 = 0; k5 < 5; k5++) {
                    const int ks = w * 5 + k5;
                    const uint32_t b0 = *reinterpret_cast<const uint32_t*>(xn + ks * 16 + 2 * t);
                    const uint32_t b1 = *reinterpret_cast<const uint32_t*>(xn + ks * 16 + 2 * t + 8);
                    const int krow = ks * 16 + (lane & 7) + ((lane >> 4) & 1) * 8;
                    uint32_t a[4];
                    ldmatrix4t(a, sbase + OFF_W1 + krow * 32 + ((lane >> 3) & 1) * 16);
                    mma16816(ch4, a[0], a[1], a[2], a[3], b0, b1);
                }
                if (t == 0) { oscr[w * 16 + g] = ch4[0]; oscr[w * 16 + 8 + g] = ch4[2]; }
            }
            __syncthreads();
            if (tid < 16) {
                float sum = 0.f;
#pragma unroll
                for (int i = 0; i < 8; i++) sum += oscr[i * 16 + tid];
                const float u = bf16r(bf16r(sum) + __bfloat162float(hs[16 + tid]));
                const float inner = 0.7978845608028654f * (u + 0.044715f * u * u * u);
                const float th = 1.0f - __fdividef(2.0f, ex2(inner * (2.0f * LOG2E)) + 1.0f);
                hs[tid] = __float2bfloat16_rn(0.5f * u * (1.0f + th));
            }
            __syncthreads();
            {
                const uint32_t b0 = *reinterpret_cast<const uint32_t*>(hs + 2 * t);
                const uint32_t b1 = *reinterpret_cast<const uint32_t*>(hs + 2 * t + 8);
                const int krow = (lane & 7) + ((lane >> 4) & 1) * 8;
#pragma unroll
                for (int i = 0; i < 5; i++) {
                    const int ch = 2 * (w * 5 + i) + ((lane >> 3) & 1);
                    uint32_t a[4];
                    float co[4] = {0.f, 0.f, 0.f, 0.f};
                    ldmatrix4t(a, sbase + OFF_W2 + krow * 1280 + ((ch ^ (lane & 7)) << 4));
                    mma16816(co, a[0], a[1], a[2], a[3], b0, b1);
                    if (t == 0) {
                        oscr[256 + (w * 5 + i) * 16 + g] = co[0];
                        oscr[256 + (w * 5 + i) * 16 + 8 + g] = co[2];
                    }
                }
                __syncwarp();
                if (lane < 20) {
                    const float4 v4 = *reinterpret_cast<const float4*>(oscr + 256 + w * 80 + lane * 4);
                    red_add_v4(acc + w * 80 + lane * 4, v4.x, v4.y, v4.z, v4.w);
                }
            }
        }
        if (s < 3) grid_barrier(base + NCTA * (s + 1));
    }
    __syncthreads();
    if (tid == 0) {
        __threadfence();
        const unsigned old = atomicAdd(&g_ctr, 1u);
        s_flag[1] = (old == base + 4 * NCTA - 1) ? 1u : 0u;
        __threadfence();
    }
    __syncthreads();
    if (s_flag[1]) {
        for (int e = tid; e < D_MODEL; e += NT) {
            float a = 0.f;
#pragma unroll
            for (int i = 0; i < NREP; i++) a += __ldcg(&g_acc[3][i][e]);
            const float o = bf16r(bf16r(a) + __bfloat162float(b2s[e]));
            P.out[e] = __float2bfloat16_rn(__bfloat162float(xs[e]) + o);
        }
    }
}

}

extern "C" void kernel_launch(void* const* d_in, const int* in_sizes, int n_in,
                              void* d_out, int out_size) {
    Params P;
    P.x = (const bf16*)d_in[0];
    P.kc = (const bf16*)d_in[1];
    P.vc = (const bf16*)d_in[2];
    P.wq = (const bf16*)d_in[3];
    P.wo = (const bf16*)d_in[4];
    P.w1 = (const bf16*)d_in[6];
    P.b1 = (const bf16*)d_in[7];
    P.w2 = (const bf16*)d_in[8];
    P.b2 = (const bf16*)d_in[9];
    P.out = (bf16*)d_out;

    cudaFuncSetAttribute(fused_kernel, cudaFuncAttributeMaxDynamicSharedMemorySize, SMEM_BYTES);

    typedef CUresult (*EncodeFn)(CUtensorMap*, CUtensorMapDataType, cuuint32_t, void*, const cuuint64_t*, const cuuint64_t*,
                                 const cuuint32_t*, const cuuint32_t*, CUtensorMapInterleave, CUtensorMapSwizzle,
                                 CUtensorMapL2promotion, CUtensorMapFloatOOBfill);
    void* fn = nullptr;
    cudaDriverEntryPointQueryResult qres;
    cudaGetDriverEntryPoint("cuTensorMapEncodeTiled", &fn, cudaEnableDefault, &qres);
    EncodeFn encode = (EncodeFn)fn;
    CUtensorMap tm_wq, tm_wo;
    {
        cuuint64_t dims[2] = {(cuuint64_t)(NHEAD * DH), (cuuint64_t)D_MODEL};
        cuuint64_t strides[1] = {(cuuint64_t)(NHEAD * DH * 2)};
        cuuint32_t box[2] = {64, 128};
        cuuint32_t es[2] = {1, 1};
        encode(&tm_wq, CU_TENSOR_MAP_DATA_TYPE_BFLOAT16, 2, (void*)P.wq, dims, strides, box, es, CU_TENSOR_MAP_INTERLEAVE_NONE,
               CU_TENSOR_MAP_SWIZZLE_128B, CU_TENSOR_MAP_L2_PROMOTION_NONE, CU_TENSOR_MAP_FLOAT_OOB_FILL_NONE);
    }
    {
        cuuint64_t dims[2] = {(cuuint64_t)D_MODEL, (cuuint64_t)(NHEAD * DH)};
        cuuint64_t strides[1] = {(cuuint64_t)(D_MODEL * 2)};
        cuuint32_t box[2] = {64, 64};
        cuuint32_t es[2] = {1, 1};
        encode(&tm_wo, CU_TENSOR_MAP_DATA_TYPE_BFLOAT16, 2, (void*)P.wo, dims, strides, box, es, CU_TENSOR_MAP_INTERLEAVE_NONE,
               CU_TENSOR_MAP_SWIZZLE_128B, CU_TENSOR_MAP_L2_PROMOTION_NONE, CU_TENSOR_MAP_FLOAT_OOB_FILL_NONE);
    }

    cudaLaunchConfig_t cfg = {};
    cfg.gridDim = dim3(NCTA);
    cfg.blockDim = dim3(NT);
    cfg.dynamicSmemBytes = SMEM_BYTES;
    cfg.stream = cudaStreamPerThread;
    cudaLaunchAttribute at[2];
    at[0].id = cudaLaunchAttributeClusterDimension;
    at[0].val.clusterDim.x = 2; at[0].val.clusterDim.y = 1; at[0].val.clusterDim.z = 1;
    at[1].id = cudaLaunchAttributeCooperative;
    at[1].val.cooperative = 1;
    cfg.attrs = at;
    cfg.numAttrs = 2;
    cudaLaunchKernelEx(&cfg, fused_kernel, P, tm_wq, tm_wo);
}
```

```cpp
#include <cuda_runtime.h>
#include <cuda.h>
#include <cuda_bf16.h>
#include <stdint.h>

typedef __nv_bfloat16 bf16;

namespace {

constexpr int D_MODEL = 640;
constexpr int NHEAD = 32;
constexpr int SEQ = 4096;
constexpr int DH = 128;
constexpr int FF = 1728;
constexpr int NCTA = 128;
constexpr int NT = 256;
constexpr int KREG_TILES = 5;
constexpr int KSM_TILES = 3;
constexpr int MLP_UNITS = 16;
constexpr int MLP_CTAS = FF / MLP_UNITS;

constexpr int OFF_STAGE = 0;
constexpr int OFF_W2 = 81920;
constexpr int OFF_W1 = OFF_W2 + 20480;
constexpr int OFF_K = OFF_W1 + 20480;
constexpr int OFF_XS = OFF_K + 98304;
constexpr int OFF_XN = OFF_XS + 1280;
constexpr int OFF_O = OFF_XN + 1280;
constexpr int OFF_P = OFF_O + 4096;
constexpr int OFF_Q = OFF_P + 2048;
constexpr int OFF_OEX = OFF_Q + 256;
constexpr int OFF_STAT = OFF_OEX + 512;
constexpr int OFF_RED = OFF_STAT + 80;
constexpr int OFF_HS = OFF_RED + 96;
constexpr int OFF_B2 = OFF_HS + 320;
constexpr int OFF_XBAR = OFF_B2 + 1280;
constexpr int SMEM_BYTES = OFF_XBAR + 16;

static_assert(SMEM_BYTES <= 232448, "smem");
constexpr int NREP = 8;
constexpr int VL = 2;
constexpr int NVB = 2;
constexpr unsigned SPIN_LIMIT = 1u << 24;

__device__ unsigned int g_ctr;
__device__ float g_acc[4][NREP][D_MODEL];
__device__ uint4 g_ml[2][NCTA];

struct Params {
    const bf16* x; const bf16* kc; const bf16* vc; const bf16* wq; const bf16* wo;
    const bf16* w1; const bf16* b1; const bf16* w2; const bf16* b2; bf16* out;
};

__device__ __forceinline__ float bf16r(float x) { return __bfloat162float(__float2bfloat16_rn(x)); }
__device__ __forceinline__ float bflo(uint32_t u) { return __uint_as_float(u << 16); }
__device__ __forceinline__ float bfhi(uint32_t u) { return __uint_as_float(u & 0xffff0000u); }

__device__ __forceinline__ uint32_t smem_u32(const void* p) { return (uint32_t)__cvta_generic_to_shared(p); }

__device__ __forceinline__ void mbar_init(uint32_t bar, uint32_t cnt) {
    asm volatile("mbarrier.init.shared::cta.b64 [%0], %1;" :: "r"(bar), "r"(cnt) : "memory");
}
__device__ __forceinline__ void mbar_expect_tx(uint32_t bar, uint32_t bytes) {
    asm volatile("mbarrier.arrive.expect_tx.shared::cta.b64 _, [%0], %1;" :: "r"(bar), "r"(bytes) : "memory");
}
__device__ __forceinline__ void mbar_wait(uint32_t bar, uint32_t parity) {
    unsigned it = 0;
    while (true) {
        uint32_t ok;
        asm volatile("{\n\t.reg .pred p;\n\tmbarrier.try_wait.parity.shared::cta.b64 p, [%1], %2;\n\tselp.u32 %0, 1, 0, p;\n\t}"
                     : "=r"(ok) : "r"(bar), "r"(parity) : "memory");
        if (ok) break;
        if (++it > SPIN_LIMIT) __trap();
    }
}
__device__ __forceinline__ void tma_2d_hint(uint32_t dst, const CUtensorMap* tm, int c0, int c1, uint32_t bar, uint64_t pol) {
    asm volatile("cp.async.bulk.tensor.2d.shared::cluster.global.mbarrier::complete_tx::bytes.L2::cache_hint [%0], [%1, {%3, %4}], [%2], %5;"
                 :: "r"(dst), "l"(tm), "r"(bar), "r"(c0), "r"(c1), "l"(pol) : "memory");
}
__device__ __forceinline__ void bulk_prefetch_l2(const void* src, uint32_t bytes) {
    asm volatile("cp.async.bulk.prefetch.L2.global [%0], %1;" :: "l"(src), "r"(bytes) : "memory");
}
__device__ __forceinline__ float ex2(float x) { float y; asm("ex2.approx.ftz.f32 %0, %1;" : "=f"(y) : "f"(x)); return y; }
__device__ __forceinline__ void cp_async16_hint(uint32_t dst, const void* src, uint64_t pol) {
    asm volatile("cp.async.cg.shared.global.L2::cache_hint [%0], [%1], 16, %2;" :: "r"(dst), "l"(src), "l"(pol) : "memory");
}
__device__ __forceinline__ void cp_async_wait_all() { asm volatile("cp.async.wait_all;" ::: "memory"); }
__device__ __forceinline__ void cp_async_commit() { asm volatile("cp.async.commit_group;" ::: "memory"); }
template <int N> __device__ __forceinline__ void cp_async_wait_group() { asm volatile("cp.async.wait_group %0;" :: "n"(N) : "memory"); }

__device__ __forceinline__ void ldg128_hint(uint32_t (&r)[4], const void* p, uint64_t pol) {
    asm volatile("ld.global.nc.L1::no_allocate.L2::cache_hint.v4.u32 {%0,%1,%2,%3}, [%4], %5;"
                 : "=r"(r[0]), "=r"(r[1]), "=r"(r[2]), "=r"(r[3]) : "l"(p), "l"(pol));
}
__device__ __forceinline__ void mma16816(float (&c)[4], uint32_t a0, uint32_t a1, uint32_t a2, uint32_t a3,
                                         uint32_t b0, uint32_t b1) {
    asm volatile("mma.sync.aligned.m16n8k16.row.col.f32.bf16.bf16.f32 {%0,%1,%2,%3}, {%4,%5,%6,%7}, {%8,%9}, {%0,%1,%2,%3};"
                 : "+f"(c[0]), "+f"(c[1]), "+f"(c[2]), "+f"(c[3])
                 : "r"(a0), "r"(a1), "r"(a2), "r"(a3), "r"(b0), "r"(b1));
}
__device__ __forceinline__ void ldmatrix4(uint32_t (&r)[4], uint32_t addr) {
    asm volatile("ldmatrix.sync.aligned.m8n8.x4.shared.b16 {%0,%1,%2,%3}, [%4];"
                 : "=r"(r[0]), "=r"(r[1]), "=r"(r[2]), "=r"(r[3]) : "r"(addr) : "memory");
}
__device__ __forceinline__ void red_add_v4(float* p, float a, float b, float c, float d) {
    asm volatile("red.global.add.v4.f32 [%0], {%1,%2,%3,%4};" :: "l"(p), "f"(a), "f"(b), "f"(c), "f"(d) : "memory");
}
__device__ __forceinline__ unsigned ld_acquire(const unsigned* p) {
    unsigned v; asm volatile("ld.acquire.gpu.global.u32 %0, [%1];" : "=r"(v) : "l"(p) : "memory"); return v;
}
__device__ __forceinline__ uint32_t mapa(uint32_t addr, uint32_t rank) {
    uint32_t r; asm volatile("mapa.shared::cluster.u32 %0, %1, %2;" : "=r"(r) : "r"(addr), "r"(rank)); return r;
}
__device__ __forceinline__ void st_async_b32(uint32_t addr, uint32_t v, uint32_t bar) {
    asm volatile("st.async.weak.shared::cluster.mbarrier::complete_tx::bytes.b32 [%0], %1, [%2];" :: "r"(addr), "r"(v), "r"(bar) : "memory");
}
__device__ __forceinline__ float warp_sum(float v) {
#pragma unroll
    for (int o = 16; o > 0; o >>= 1) v += __shfl_xor_sync(0xffffffffu, v, o);
    return v;
}

__device__ __forceinline__ void grid_barrier(unsigned target) {
    __syncthreads();
    if (threadIdx.x == 0) {
        __threadfence();
        atomicAdd(&g_ctr, 1u);
        unsigned it = 0;
        while ((int)(ld_acquire(&g_ctr) - target) < 0) { if (++it > SPIN_LIMIT) __trap(); }
    }
    __syncthreads();
}

constexpr float LOG2E = 1.4426950408889634f;

__device__ __forceinline__ void ldmatrix4t(uint32_t (&r)[4], uint32_t addr) {
    asm volatile("ldmatrix.sync.aligned.m8n8.x4.trans.shared.b16 {%0,%1,%2,%3}, [%4];"
                 : "=r"(r[0]), "=r"(r[1]), "=r"(r[2]), "=r"(r[3]) : "r"(addr) : "memory");
}
__device__ __forceinline__ uint32_t pack_bf16(float lo, float hi) {
    uint32_t r; asm("cvt.rn.bf16x2.f32 %0, %1, %2;" : "=r"(r) : "f"(hi), "f"(lo)); return r;
}

__global__ void __launch_bounds__(NT, 1) fused_kernel(const Params P, const __grid_constant__ CUtensorMap tm_wq,
                                                        const __grid_constant__ CUtensorMap tm_wo) {
    extern __shared__ __align__(1024) unsigned char sm[];
    const int tid = threadIdx.x, lane = tid & 31, w = tid >> 5;
    const int g = lane >> 2, t = lane & 3;
    const int b = blockIdx.x, h = b >> 2, c = b & 3, r = b & 1;
    const uint32_t sbase = smem_u32(sm);
    bf16* xs = reinterpret_cast<bf16*>(sm + OFF_XS);
    bf16* xn = reinterpret_cast<bf16*>(sm + OFF_XN);
    bf16* b2s = reinterpret_cast<bf16*>(sm + OFF_B2);
    float* oscr = reinterpret_cast<float*>(sm + OFF_O);
    bf16* qs = reinterpret_cast<bf16*>(sm + OFF_Q);
    float* oex = reinterpret_cast<float*>(sm + OFF_OEX);
    float* stat = reinterpret_cast<float*>(sm + OFF_STAT);
    float* red = reinterpret_cast<float*>(sm + OFF_RED);
    bf16* hs = reinterpret_cast<bf16*>(sm + OFF_HS);
    volatile unsigned* s_flag = reinterpret_cast<volatile unsigned*>(sm + OFF_STAT + 64);
    const uint32_t bar_stage = sbase + OFF_STAT + 72;
    if (tid < D_MODEL / 8) *reinterpret_cast<uint4*>(xs + tid * 8) = __ldg(reinterpret_cast<const uint4*>(P.x) + tid);
    else if (tid < D_MODEL / 4) *reinterpret_cast<uint4*>(b2s + (tid - 80) * 8) = __ldg(reinterpret_cast<const uint4*>(P.b2) + (tid - 80));
    else if (tid < 162) { if (b < MLP_CTAS) *reinterpret_cast<uint4*>(hs + 16 + (tid - 160) * 8) = __ldg(reinterpret_cast<const uint4*>(P.b1 + b * MLP_UNITS) + (tid - 160)); }
    else if (tid == 192) s_flag[0] = ld_acquire(&g_ctr) >> 9;
    uint64_t pol_first;
    asm volatile("createpolicy.fractional.L2::evict_first.b64 %0, 1.0;" : "=l"(pol_first));
    uint64_t pol_norm;
    asm volatile("createpolicy.fractional.L2::evict_normal.b64 %0, 1.0;" : "=l"(pol_norm));

    const size_t kv_off = (size_t)(h * SEQ + c * 1024 + w * 128) * DH;
    if (tid == 224) {
        mbar_init(bar_stage, 1);
        mbar_init(sbase + OFF_XBAR, 1);
        mbar_init(sbase + OFF_XBAR + 8, 1);
        asm volatile("fence.mbarrier_init.release.cluster;" ::: "memory");
        asm volatile("fence.proxy.async.shared::cta;" ::: "memory");
        mbar_expect_tx(bar_stage, 81920);
#pragma unroll
        for (int i = 0; i < 5; i++) tma_2d_hint(sbase + OFF_STAGE + i * 16384, &tm_wq, h * DH + r * 64, i * 128, bar_stage, pol_first);
    }
    const uint32_t kb = sbase + OFF_K + w * (KSM_TILES * 16 * 256);
    {
        const bf16* kq = P.kc + kv_off + KREG_TILES * 16 * DH;
#pragma unroll 1
        for (int it = 0; it < KSM_TILES * 8; it++) {
            const int idx = it * 32 + lane;
            const int row = idx >> 4, ch = idx & 15;
            cp_async16_hint(kb + row * 256 + ((ch ^ (row & 7)) << 4), kq + row * DH + ch * 8, pol_first);
        }
    }
    cp_async_commit();
    if (b == 1) for (int e = tid; e < 3 * NREP * D_MODEL; e += NT) (&g_acc[1][0][0])[e] = 0.f;
    uint32_t kreg[KREG_TILES][2][4][4];
    __syncthreads();
    asm volatile("barrier.cluster.arrive.relaxed.aligned;" ::: "memory");
    const unsigned epoch = s_flag[0];
    const unsigned base = epoch << 9;

#pragma unroll 1
    for (int s = 0; s < 4; s++) {
        {
            float v[4] = {0.f, 0.f, 0.f, 0.f};
            if (tid < D_MODEL / 4) {
                const uint2 xr = *reinterpret_cast<const uint2*>(xs + tid * 4);
                v[0] = bflo(xr.x); v[1] = bfhi(xr.x); v[2] = bflo(xr.y); v[3] = bfhi(xr.y);
                if (s != 0) {
                    float4 a = __ldcg(reinterpret_cast<const float4*>(&g_acc[s - 1][0][0]) + tid);
#pragma unroll
                    for (int i = 1; i < NREP; i++) {
                        const float4 a2 = __ldcg(reinterpret_cast<const float4*>(&g_acc[s - 1][i][0]) + tid);
                        a.x += a2.x; a.y += a2.y; a.z += a2.z; a.w += a2.w;
                    }
                    a.x = bf16r(a.x); a.y = bf16r(a.y); a.z = bf16r(a.z); a.w = bf16r(a.w);
                    if (s == 2) {
                        const uint2 br = *reinterpret_cast<const uint2*>(b2s + tid * 4);
                        a.x = bf16r(a.x + bflo(br.x)); a.y = bf16r(a.y + bfhi(br.x));
                        a.z = bf16r(a.z + bflo(br.y)); a.w = bf16r(a.w + bfhi(br.y));
                    }
                    v[0] = bf16r(v[0] + a.x); v[1] = bf16r(v[1] + a.y); v[2] = bf16r(v[2] + a.z); v[3] = bf16r(v[3] + a.w);
                    *reinterpret_cast<uint2*>(xs + tid * 4) = make_uint2(pack_bf16(v[0], v[1]), pack_bf16(v[2], v[3]));
                }
            }
            if (s == 2 && b == 0) {
                for (int e = tid; e < NREP * D_MODEL; e += NT) (&g_acc[0][0][0])[e] = 0.f;
            }
#pragma unroll 1
            for (int rep = 0; rep <= (s & 1); rep++) {
                float mean = 0.25f * ((v[0] + v[1]) + (v[2] + v[3]));
                float m2 = (v[0] - mean) * (v[0] - mean) + (v[1] - mean) * (v[1] - mean) +
                           (v[2] - mean) * (v[2] - mean) + (v[3] - mean) * (v[3] - mean);
                float hn = 2.f;
#pragma unroll
                for (int o = 1; o < 32; o <<= 1) {
                    const float mo = __shfl_xor_sync(0xffffffffu, mean, o);
                    const float qo = __shfl_xor_sync(0xffffffffu, m2, o);
                    const float d = mo - mean;
                    m2 = m2 + qo + d * d * hn;
                    mean = 0.5f * (mean + mo);
                    hn *= 2.f;
                }
                float* rd = red + rep * 12;
                if (lane == 0 && w < 5) { rd[2 * w] = mean; rd[2 * w + 1] = m2; }
                __syncthreads();
                float gm = 0.f, gq = 0.f;
#pragma unroll
                for (int i = 0; i < 5; i++) { gm += rd[2 * i]; gq += rd[2 * i + 1]; }
                gm *= 0.2f;
#pragma unroll
                for (int i = 0; i < 5; i++) { const float d = rd[2 * i] - gm; gq += 128.f * d * d; }
                const float mb = bf16r(gm);
                const float den = bf16r(sqrtf(bf16r(bf16r(gq * (1.0f / D_MODEL)) + 1e-5f)));
#pragma unroll
                for (int i = 0; i < 4; i++) v[i] = bf16r(__fdividef(bf16r(v[i] - mb), den));
            }
            if (tid < D_MODEL / 4)
                *reinterpret_cast<uint2*>(xn + tid * 4) = make_uint2(pack_bf16(v[0], v[1]), pack_bf16(v[2], v[3]));
        }
        if (s == 1) cp_async_wait_all();
        __syncthreads();
        float* acc = &g_acc[s][b & (NREP - 1)][0];

        if (!(s & 1)) {
            const int pass = s >> 1;
            mbar_wait(bar_stage, 0);
            {
                float cq[4][4];
#pragma unroll
                for (int i = 0; i < 4; i++) { cq[i][0] = cq[i][1] = cq[i][2] = cq[i][3] = 0.f; }
#pragma unroll
                for (int k5 = 0; k5 < 5; k5++) {
                    const int ks = w * 5 + k5;
                    const uint32_t b0 = *reinterpret_cast<const uint32_t*>(xn + ks * 16 + 2 * t);
                    const uint32_t b1 = *reinterpret_cast<const uint32_t*>(xn + ks * 16 + 2 * t + 8);
                    const int krow = ks * 16 + (lane & 7) + ((lane >> 4) & 1) * 8;
#pragma unroll
                    for (int mt = 0; mt < 4; mt++) {
                        uint32_t a[4];
                        ldmatrix4t(a, sbase + OFF_STAGE + krow * 128 + (((2 * mt + ((lane >> 3) & 1)) ^ (lane & 7)) << 4));
                        mma16816(cq[mt], a[0], a[1], a[2], a[3], b0, b1);
                    }
                }
                if (t == 0) {
#pragma unroll
                    for (int mt = 0; mt < 4; mt++) { oscr[w * 64 + mt * 16 + g] = cq[mt][0]; oscr[w * 64 + mt * 16 + 8 + g] = cq[mt][2]; }
                }
            }
            __syncthreads();
            if (s == 0) asm volatile("barrier.cluster.wait.aligned;" ::: "memory");
            if (tid < 32) {
                float s0 = 0.f, s1 = 0.f;
#pragma unroll
                for (int i = 0; i < 8; i++) { const float2 v2 = *reinterpret_cast<const float2*>(oscr + i * 64 + 2 * tid); s0 += v2.x; s1 += v2.y; }
                const uint32_t qp = pack_bf16(s0, s1);
                *reinterpret_cast<uint32_t*>(qs + r * 64 + 2 * tid) = qp;
                st_async_b32(mapa(sbase + OFF_Q + (r * 64 + 2 * tid) * 2, r ^ 1), qp, mapa(sbase + OFF_XBAR, r ^ 1));
                if (tid == 0) { mbar_expect_tx(sbase + OFF_XBAR, 128); mbar_expect_tx(sbase + OFF_XBAR + 8, 256); }
            }
            const uint32_t vland = sbase + OFF_STAGE + w * (VL * 4096);
#pragma unroll 1
            for (int it = 0; it < VL * 8; it++) {
                const int idx = it * 32 + lane;
                const int row = idx >> 4, ch = idx & 15;
                cp_async16_hint(vland + row * 256 + ((ch ^ (row & 7)) << 4), P.vc + kv_off + row * DH + ch * 8, pol_first);
            }
            cp_async_commit();
            if (s == 0) {
                const bf16* kp = P.kc + kv_off + (g * DH + t * 8);
#pragma unroll
                for (int i = 0; i < KREG_TILES; i++)
#pragma unroll
                    for (int hh = 0; hh < 2; hh++)
#pragma unroll
                        for (int j = 0; j < 4; j++)
                            ldg128_hint(kreg[i][hh][j], kp + (i * 16 + hh * 8) * DH + j * 32, pol_first);
            }
            __syncthreads();
            mbar_wait(sbase + OFF_XBAR, pass);

            float sc[8][2];
            {
                float cacc[KREG_TILES][4];
#pragma unroll
                for (int i = 0; i < KREG_TILES; i++) { cacc[i][0] = cacc[i][1] = cacc[i][2] = cacc[i][3] = 0.f; }
#pragma unroll
                for (int j = 0; j < 4; j++) {
                    const uint4 qv = *reinterpret_cast<const uint4*>(qs + j * 32 + t * 8);
#pragma unroll
                    for (int i = 0; i < KREG_TILES; i++) {
                        mma16816(cacc[i], kreg[i][0][j][0], kreg[i][1][j][0], kreg[i][0][j][1], kreg[i][1][j][1], qv.x, qv.y);
                        mma16816(cacc[i], kreg[i][0][j][2], kreg[i][1][j][2], kreg[i][0][j][3], kreg[i][1][j][3], qv.z, qv.w);
                    }
                }
#pragma unroll
                for (int i = 0; i < KREG_TILES; i++) { sc[i][0] = cacc[i][0]; sc[i][1] = cacc[i][2]; }
            }
            {
                if (s == 0) {
                    if (lane == 0) bulk_prefetch_l2(P.vc + kv_off + VL * 16 * DH, (8 - VL) * 4096);
                    cp_async_wait_group<1>();
                    __syncwarp();
                }
                float cacc[KSM_TILES][4];
#pragma unroll
                for (int tt = 0; tt < KSM_TILES; tt++) { cacc[tt][0] = cacc[tt][1] = cacc[tt][2] = cacc[tt][3] = 0.f; }
                const int row0 = (lane & 7) + ((lane >> 3) & 1) * 8;
#pragma unroll 4
                for (int ks = 0; ks < 8; ks++) {
                    const uint32_t b0 = *reinterpret_cast<const uint32_t*>(qs + ks * 16 + 2 * t);
                    const uint32_t b1 = *reinterpret_cast<const uint32_t*>(qs + ks * 16 + 2 * t + 8);
                    const int ch = 2 * ks + (lane >> 4);
                    const uint32_t ad = kb + row0 * 256 + ((ch ^ (lane & 7)) << 4);
#pragma unroll
                    for (int tt = 0; tt < KSM_TILES; tt++) {
                        uint32_t a[4];
                        ldmatrix4(a, ad + tt * 4096);
                        mma16816(cacc[tt], a[0], a[1], a[2], a[3], b0, b1);
                    }
                }
#pragma unroll
                for (int tt = 0; tt < KSM_TILES; tt++) { sc[KREG_TILES + tt][0] = cacc[tt][0]; sc[KREG_TILES + tt][1] = cacc[tt][2]; }
            }
            bf16* pw = reinterpret_cast<bf16*>(sm + OFF_P + w * 256);
            {
                float s4[4];
#pragma unroll
                for (int q2 = 0; q2 < 4; q2++) {
                    const int i = q2 >> 1, k2 = q2 & 1;
                    const float v01 = (t & 1) ? sc[2 + i][k2] : sc[i][k2];
                    const float v23 = (t & 1) ? sc[6 + i][k2] : sc[4 + i][k2];
                    s4[q2] = (t & 2) ? v23 : v01;
                }
                float mx = -INFINITY;
#pragma unroll
                for (int q2 = 0; q2 < 4; q2++) {
                    s4[q2] = bf16r(bf16r(s4[q2]) * 0.08838834764831845f);
                    mx = fmaxf(mx, s4[q2]);
                }
#pragma unroll
                for (int o = 1; o < 32; o <<= 1) mx = fmaxf(mx, __shfl_xor_sync(0xffffffffu, mx, o));
                float l = 0.f;
#pragma unroll
                for (int q2 = 0; q2 < 4; q2++) {
                    const bf16 pb = __float2bfloat16_rn(ex2((s4[q2] - mx) * LOG2E));
                    l += __bfloat162float(pb);
                    pw[(2 * t + (q2 >> 1)) * 16 + (q2 & 1) * 8 + g] = pb;
                }
                l = warp_sum(l);
                if (lane == 0) { stat[2 * w] = mx; stat[2 * w + 1] = l; }
            }
            __syncthreads();
            float m_cta = stat[0];
#pragma unroll
            for (int i = 1; i < 8; i++) m_cta = fmaxf(m_cta, stat[2 * i]);
            const float wfac = ex2((stat[2 * w] - m_cta) * LOG2E);
            if (tid == 0) {
                float l_cta = 0.f;
#pragma unroll
                for (int i = 0; i < 8; i++) l_cta += stat[2 * i + 1] * ex2((stat[2 * i] - m_cta) * LOG2E);
                asm volatile("st.relaxed.gpu.global.v4.u32 [%0], {%1,%2,%3,%4};" :: "l"(&g_ml[pass][b]),
                             "r"(__float_as_uint(m_cta)), "r"(__float_as_uint(l_cta)), "r"(epoch * 2 + pass + 1), "r"(0u) : "memory");
            }

            {
                const bf16* vbase = P.vc + kv_off + (4 * t) * DH + g * 8;
                float* ow = oscr + w * 128;
                constexpr int NK = 8 - VL;
                static_assert(NK % NVB == 0, "NVB");
                uint32_t vbuf[NVB][4][4];
#pragma unroll
                for (int u = 0; u < NVB - 1; u++)
#pragma unroll
                    for (int i = 0; i < 4; i++) ldg128_hint(vbuf[u][i], vbase + ((VL + u) * 16 + i) * DH, pol_norm);
                cp_async_wait_all();
                __syncwarp();
#pragma unroll 4
                for (int mt = 0; mt < 8; mt++) {
                    float cl[4] = {0.f, 0.f, 0.f, 0.f};
#pragma unroll
                    for (int kt = 0; kt < VL; kt++) {
                        const uint32_t b0 = *reinterpret_cast<const uint32_t*>(pw + kt * 16 + 2 * t);
                        const uint32_t b1 = *reinterpret_cast<const uint32_t*>(pw + kt * 16 + 2 * t + 8);
                        const int row = kt * 16 + (lane & 7) + ((lane >> 4) & 1) * 8;
                        uint32_t a[4];
                        ldmatrix4t(a, vland + row * 256 + (((2 * mt + ((lane >> 3) & 1)) ^ (lane & 7)) << 4));
                        mma16816(cl, a[0], a[1], a[2], a[3], b0, b1);
                    }
                    if (t == 0) { ow[mt * 16 + g] = cl[0] * wfac; ow[mt * 16 + 8 + g] = cl[2] * wfac; }
                }
                __syncwarp();
                if (w != 7) asm volatile("bar.arrive 1, 256;" ::: "memory");
                float oacc[4][4];
#pragma unroll
                for (int i = 0; i < 4; i++) { oacc[i][0] = oacc[i][1] = oacc[i][2] = oacc[i][3] = 0.f; }
#pragma unroll 1
                for (int hf = 0; hf < 2; hf++) {
#pragma unroll 1
                    for (int k0 = 0; k0 < NK; k0 += NVB) {
                        if (w == 7 && hf == 1 && k0 == 2) {
                            asm volatile("bar.sync 1, 256;" ::: "memory");
                            if (lane == 0) {
                                mbar_expect_tx(bar_stage, 81920);
#pragma unroll 1
                                for (int i = 0; i < 10; i++) tma_2d_hint(sbase + OFF_STAGE + i * 8192, &tm_wo, i * 64, h * DH + r * 64, bar_stage, pol_first);
                            }
                            __syncwarp();
                        }
#pragma unroll
                        for (int u = 0; u < NVB; u++) {
                            const int kt = k0 + u;
                            int nk = kt + NVB - 1, nh = hf;
                            if (nk >= NK) { nk -= NK; nh = hf + 1; }
                            if (nh < 2) {
                                const bf16* vp = vbase + (VL + nk) * 16 * DH + nh * 64;
#pragma unroll
                                for (int i = 0; i < 4; i++) ldg128_hint(vbuf[(u + NVB - 1) % NVB][i], vp + i * DH, pol_norm);
                            }
                            const uint2 pb = *reinterpret_cast<const uint2*>(pw + (VL + kt) * 16 + 4 * t);
#pragma unroll
                            for (int e = 0; e < 4; e++)
                                mma16816(oacc[e], __byte_perm(vbuf[u][0][e], vbuf[u][1][e], 0x5410), __byte_perm(vbuf[u][0][e], vbuf[u][1][e], 0x7632),
                                         __byte_perm(vbuf[u][2][e], vbuf[u][3][e], 0x5410), __byte_perm(vbuf[u][2][e], vbuf[u][3][e], 0x7632), pb.x, pb.y);
                        }
                    }
                    if (t == 0) {
                        float* o2 = ow + hf * 64 + g * 8;
                        float4 u0 = *reinterpret_cast<float4*>(o2), u1 = *reinterpret_cast<float4*>(o2 + 4);
                        u0.x += oacc[0][0] * wfac; u0.y += oacc[0][2] * wfac; u0.z += oacc[1][0] * wfac; u0.w += oacc[1][2] * wfac;
                        u1.x += oacc[2][0] * wfac; u1.y += oacc[2][2] * wfac; u1.z += oacc[3][0] * wfac; u1.w += oacc[3][2] * wfac;
                        *reinterpret_cast<float4*>(o2) = u0;
                        *reinterpret_cast<float4*>(o2 + 4) = u1;
                    }
#pragma unroll
                    for (int i = 0; i < 4; i++) { oacc[i][0] = oacc[i][1] = oacc[i][2] = oacc[i][3] = 0.f; }
                }
            }
            if (s == 0 && b < MLP_CTAS) {
#pragma unroll 1
                for (int idx = tid; idx < 2 * D_MODEL; idx += NT) {
                    const int row = idx >> 1, hf = idx & 1;
                    cp_async16_hint(sbase + OFF_W1 + row * 32 + hf * 16, P.w1 + (size_t)row * FF + b * MLP_UNITS + hf * 8, pol_first);
                    const int r2 = idx / 80, ch = idx - r2 * 80;
                    cp_async16_hint(sbase + OFF_W2 + r2 * 1280 + ((ch ^ (r2 & 7)) << 4), P.w2 + (size_t)(b * MLP_UNITS) * D_MODEL + idx * 8, pol_first);
                }
                cp_async_commit();
            }
            float scale = 0.f;
            if (tid < 128) {
                uint4 rec[4];
                {
                    unsigned it = 0;
                    const unsigned tag = epoch * 2 + pass + 1;
                    while (true) {
#pragma unroll
                        for (int i = 0; i < 4; i++)
                            asm volatile("ld.relaxed.gpu.global.v4.u32 {%0,%1,%2,%3}, [%4];"
                                         : "=r"(rec[i].x), "=r"(rec[i].y), "=r"(rec[i].z), "=r"(rec[i].w)
                                         : "l"(&g_ml[pass][(b & ~3) + i]) : "memory");
                        if (rec[0].z == tag && rec[1].z == tag && rec[2].z == tag && rec[3].z == tag) break;
                        if (++it > SPIN_LIMIT) __trap();
                    }
                }
                const float M = fmaxf(fmaxf(__uint_as_float(rec[0].x), __uint_as_float(rec[1].x)),
                                      fmaxf(__uint_as_float(rec[2].x), __uint_as_float(rec[3].x)));
                float L = 0.f;
#pragma unroll
                for (int i = 0; i < 4; i++) L += __uint_as_float(rec[i].y) * ex2((__uint_as_float(rec[i].x) - M) * LOG2E);
                scale = __fdividef(ex2((m_cta - M) * LOG2E), L);
            }
            __syncthreads();
            if (tid < 128) {
                float sum = 0.f;
#pragma unroll
                for (int i = 0; i < 8; i++) sum += oscr[i * 128 + tid];
                if ((tid >> 6) == r) oex[r * 64 + (tid & 63)] = sum * scale;
                else st_async_b32(mapa(sbase + OFF_OEX + (r * 64 + (tid & 63)) * 4, r ^ 1), __float_as_uint(sum * scale), mapa(sbase + OFF_XBAR + 8, r ^ 1));
            }
            __syncthreads();
            if (tid < 64) {
                mbar_wait(sbase + OFF_XBAR + 8, pass);
                const float o = oex[tid] + oex[64 + tid];
                const bf16 hi = __float2bfloat16_rn(o);
                hs[32 + tid] = hi;
                hs[96 + tid] = __float2bfloat16_rn(o - __bfloat162float(hi));
            }
            mbar_wait(bar_stage, 1);
            __syncthreads();
            {
                float co[5][4];
#pragma unroll
                for (int i = 0; i < 5; i++) { co[i][0] = co[i][1] = co[i][2] = co[i][3] = 0.f; }
#pragma unroll 1
                for (int ks = 0; ks < 4; ks++) {
                    uint32_t b0 = 0, b1 = 0;
                    if (g < 2) {
                        b0 = *reinterpret_cast<const uint32_t*>(hs + 32 + g * 64 + ks * 16 + 2 * t);
                        b1 = *reinterpret_cast<const uint32_t*>(hs + 32 + g * 64 + ks * 16 + 2 * t + 8);
                    }
                    const int krow = ks * 16 + (lane & 7) + ((lane >> 4) & 1) * 8;
#pragma unroll
                    for (int i = 0; i < 5; i++) {
                        const int ch = 2 * (w * 5 + i) + ((lane >> 3) & 1);
                        uint32_t a[4];
                        ldmatrix4t(a, sbase + OFF_STAGE + (ch >> 3) * 8192 + krow * 128 + (((ch ^ lane) & 7) << 4));
                        mma16816(co[i], a[0], a[1], a[2], a[3], b0, b1);
                    }
                }
                if (t == 0) {
#pragma unroll
                    for (int i = 0; i < 5; i++) {
                        oscr[(w * 5 + i) * 16 + g] = co[i][0] + co[i][1];
                        oscr[(w * 5 + i) * 16 + 8 + g] = co[i][2] + co[i][3];
                    }
                }
                __syncwarp();
                if (lane < 20) {
                    const float4 v4 = *reinterpret_cast<const float4*>(oscr + w * 80 + lane * 4);
                    red_add_v4(acc + w * 80 + lane * 4, v4.x, v4.y, v4.z, v4.w);
                }
            }
            if (s == 0) {
                __syncthreads();
                if (tid == 224) {
                    mbar_expect_tx(bar_stage, 81920);
#pragma unroll 1
                    for (int i = 0; i < 5; i++) tma_2d_hint(sbase + OFF_STAGE + i * 16384, &tm_wq, h * DH + r * 64, i * 128, bar_stage, pol_first);
                }
            }
        } else if (b < MLP_CTAS) {
            {
                float ch4[4] = {0.f, 0.f, 0.f, 0.f};
#pragma unroll
                for (int k5 = 0; k5 < 5; k5++) {
                    const int ks = w * 5 + k5;
                    const uint32_t b0 = *reinterpret_cast<const uint32_t*>(xn + ks * 16 + 2 * t);
                    const uint32_t b1 = *reinterpret_cast<const uint32_t*>(xn + ks * 16 + 2 * t + 8);
                    const int krow = ks * 16 + (lane & 7) + ((lane >> 4) & 1) * 8;
                    uint32_t a[4];
                    ldmatrix4t(a, sbase + OFF_W1 + krow * 32 + ((lane >> 3) & 1) * 16);
                    mma16816(ch4, a[0], a[1], a[2], a[3], b0, b1);
                }
                if (t == 0) { oscr[w * 16 + g] = ch4[0]; oscr[w * 16 + 8 + g] = ch4[2]; }
            }
            __syncthreads();
            if (tid < 16) {
                float sum = 0.f;
#pragma unroll
                for (int i = 0; i < 8; i++) sum += oscr[i * 16 + tid];
                const float u = bf16r(bf16r(sum) + __bfloat162float(hs[16 + tid]));
                const float inner = 0.7978845608028654f * (u + 0.044715f * u * u * u);
                const float th = 1.0f - __fdividef(2.0f, ex2(inner * (2.0f * LOG2E)) + 1.0f);
                hs[tid] = __float2bfloat16_rn(0.5f * u * (1.0f + th));
            }
            __syncthreads();
            {
                const uint32_t b0 = *reinterpret_cast<const uint32_t*>(hs + 2 * t);
                const uint32_t b1 = *reinterpret_cast<const uint32_t*>(hs + 2 * t + 8);
                const int krow = (lane & 7) + ((lane >> 4) & 1) * 8;
#pragma unroll
                for (int i = 0; i < 5; i++) {
                    const int ch = 2 * (w * 5 + i) + ((lane >> 3) & 1);
                    uint32_t a[4];
                    float co[4] = {0.f, 0.f, 0.f, 0.f};
                    ldmatrix4t(a, sbase + OFF_W2 + krow * 1280 + ((ch ^ (lane & 7)) << 4));
                    mma16816(co, a[0], a[1], a[2], a[3], b0, b1);
                    if (t == 0) {
                        oscr[256 + (w * 5 + i) * 16 + g] = co[0];
                        oscr[256 + (w * 5 + i) * 16 + 8 + g] = co[2];
                    }
                }
                __syncwarp();
                if (lane < 20) {
                    const float4 v4 = *reinterpret_cast<const float4*>(oscr + 256 + w * 80 + lane * 4);
                    red_add_v4(acc + w * 80 + lane * 4, v4.x, v4.y, v4.z, v4.w);
                }
            }
        }
        if (s < 3) grid_barrier(base + NCTA * (s + 1));
    }
    __syncthreads();
    if (tid == 0) {
        __threadfence();
        const unsigned old = atomicAdd(&g_ctr, 1u);
        s_flag[1] = (old == base + 4 * NCTA - 1) ? 1u : 0u;
        __threadfence();
    }
    __syncthreads();
    if (s_flag[1]) {
        for (int e = tid; e < D_MODEL; e += NT) {
            float a = 0.f;
#pragma unroll
            for (int i = 0; i < NREP; i++) a += __ldcg(&g_acc[3][i][e]);
            const float o = bf16r(bf16r(a) + __bfloat162float(b2s[e]));
            P.out[e] = __float2bfloat16_rn(__bfloat162float(xs[e]) + o);
        }
    }
}

}

extern "C" void kernel_launch(void* const* d_in, const int* in_sizes, int n_in,
                              void* d_out, int out_size) {
    Params P;
    P.x = (const bf16*)d_in[0];
    P.kc = (const bf16*)d_in[1];
    P.vc = (const bf16*)d_in[2];
    P.wq = (const bf16*)d_in[3];
    P.wo = (const bf16*)d_in[4];
    P.w1 = (const bf16*)d_in[6];
    P.b1 = (const bf16*)d_in[7];
    P.w2 = (const bf16*)d_in[8];
    P.b2 = (const bf16*)d_in[9];
    P.out = (bf16*)d_out;

    cudaFuncSetAttribute(fused_kernel, cudaFuncAttributeMaxDynamicSharedMemorySize, SMEM_BYTES);

    typedef CUresult (*EncodeFn)(CUtensorMap*, CUtensorMapDataType, cuuint32_t, void*, const cuuint64_t*, const cuuint64_t*,
                                 const cuuint32_t*, const cuuint32_t*, CUtensorMapInterleave, CUtensorMapSwizzle,
                                 CUtensorMapL2promotion, CUtensorMapFloatOOBfill);
    void* fn = nullptr;
    cudaDriverEntryPointQueryResult qres;
    cudaGetDriverEntryPoint("cuTensorMapEncodeTiled", &fn, cudaEnableDefault, &qres);
    EncodeFn encode = (EncodeFn)fn;
    CUtensorMap tm_wq, tm_wo;
    {
        cuuint64_t dims[2] = {(cuuint64_t)(NHEAD * DH), (cuuint64_t)D_MODEL};
        cuuint64_t strides[1] = {(cuuint64_t)(NHEAD * DH * 2)};
        cuuint32_t box[2] = {64, 128};
        cuuint32_t es[2] = {1, 1};
        encode(&tm_wq, CU_TENSOR_MAP_DATA_TYPE_BFLOAT16, 2, (void*)P.wq, dims, strides, box, es, CU_TENSOR_MAP_INTERLEAVE_NONE,
               CU_TENSOR_MAP_SWIZZLE_128B, CU_TENSOR_MAP_L2_PROMOTION_NONE, CU_TENSOR_MAP_FLOAT_OOB_FILL_NONE);
    }
    {
        cuuint64_t dims[2] = {(cuuint64_t)D_MODEL, (cuuint64_t)(NHEAD * DH)};
        cuuint64_t strides[1] = {(cuuint64_t)(D_MODEL * 2)};
        cuuint32_t box[2] = {64, 64};
        cuuint32_t es[2] = {1, 1};
        encode(&tm_wo, CU_TENSOR_MAP_DATA_TYPE_BFLOAT16, 2, (void*)P.wo, dims, strides, box, es, CU_TENSOR_MAP_INTERLEAVE_NONE,
               CU_TENSOR_MAP_SWIZZLE_128B, CU_TENSOR_MAP_L2_PROMOTION_NONE, CU_TENSOR_MAP_FLOAT_OOB_FILL_NONE);
    }

    cudaLaunchConfig_t cfg = {};
    cfg.gridDim = dim3(NCTA);
    cfg.blockDim = dim3(NT);
    cfg.dynamicSmemBytes = SMEM_BYTES;
    cfg.stream = cudaStreamPerThread;
    cudaLaunchAttribute at[2];
    at[0].id = cudaLaunchAttributeClusterDimension;
    at[0].val.clusterDim.x = 2; at[0].val.clusterDim.y = 1; at[0].val.clusterDim.z = 1;
    at[1].id = cudaLaunchAttributeCooperative;
    at[1].val.cooperative = 1;
    cfg.attrs = at;
    cfg.numAttrs = 2;
    cudaLaunchKernelEx(&cfg, fused_kernel, P, tm_wq, tm_wo);
}
```

```cpp
#include <cuda_runtime.h>
#include <cuda.h>
#include <cuda_bf16.h>
#include <stdint.h>

typedef __nv_bfloat16 bf16;

namespace {

constexpr int D_MODEL = 640;
constexpr int NHEAD = 32;
constexpr int SEQ = 4096;
constexpr int DH = 128;
constexpr int FF = 1728;
constexpr int NCTA = 128;
constexpr int NT = 256;
constexpr int KREG_TILES = 5;
constexpr int KSM_TILES = 3;
constexpr int MLP_UNITS = 16;
constexpr int MLP_CTAS = FF / MLP_UNITS;

constexpr int OFF_STAGE = 0;
constexpr int OFF_W2 = 81920;
constexpr int OFF_W1 = OFF_W2 + 20480;
constexpr int OFF_K = OFF_W1 + 20480;
constexpr int OFF_XS = OFF_K + 98304;
constexpr int OFF_XN = OFF_XS + 1280;
constexpr int OFF_O = OFF_XN + 1280;
constexpr int OFF_P = OFF_O + 4096;
constexpr int OFF_Q = OFF_P + 2048;
constexpr int OFF_OEX = OFF_Q + 256;
constexpr int OFF_STAT = OFF_OEX + 512;
constexpr int OFF_RED = OFF_STAT + 80;
constexpr int OFF_HS = OFF_RED + 96;
constexpr int OFF_B2 = OFF_HS + 320;
constexpr int OFF_XBAR = OFF_B2 + 1280;
constexpr int SMEM_BYTES = OFF_XBAR + 16;

static_assert(SMEM_BYTES <= 232448, "smem");
constexpr int NREP = 8;
constexpr int VL = 2;
constexpr int NVB = 2;
constexpr unsigned SPIN_LIMIT = 1u << 24;

__device__ unsigned int g_ctr;
__device__ float g_acc[4][NREP][D_MODEL];
__device__ uint4 g_ml[2][NCTA];

struct Params {
    const bf16* x; const bf16* kc; const bf16* vc; const bf16* wq; const bf16* wo;
    const bf16* w1; const bf16* b1; const bf16* w2; const bf16* b2; bf16* out;
};

__device__ __forceinline__ float bf16r(float x) { return __bfloat162float(__float2bfloat16_rn(x)); }
__device__ __forceinline__ float bflo(uint32_t u) { return __uint_as_float(u << 16); }
__device__ __forceinline__ float bfhi(uint32_t u) { return __uint_as_float(u & 0xffff0000u); }

__device__ __forceinline__ uint32_t smem_u32(const void* p) { return (uint32_t)__cvta_generic_to_shared(p); }

__device__ __forceinline__ void mbar_init(uint32_t bar, uint32_t cnt) {
    asm volatile("mbarrier.init.shared::cta.b64 [%0], %1;" :: "r"(bar), "r"(cnt) : "memory");
}
__device__ __forceinline__ void mbar_expect_tx(uint32_t bar, uint32_t bytes) {
    asm volatile("mbarrier.arrive.expect_tx.shared::cta.b64 _, [%0], %1;" :: "r"(bar), "r"(bytes) : "memory");
}
__device__ __forceinline__ void mbar_wait(uint32_t bar, uint32_t parity) {
    unsigned it = 0;
    while (true) {
        uint32_t ok;
        asm volatile("{\n\t.reg .pred p;\n\tmbarrier.try_wait.parity.shared::cta.b64 p, [%1], %2;\n\tselp.u32 %0, 1, 0, p;\n\t}"
                     : "=r"(ok) : "r"(bar), "r"(parity) : "memory");
        if (ok) break;
        if (++it > SPIN_LIMIT) __trap();
    }
}
__device__ __forceinline__ void tma_2d_hint(uint32_t dst, const CUtensorMap* tm, int c0, int c1, uint32_t bar, uint64_t pol) {
    asm volatile("cp.async.bulk.tensor.2d.shared::cluster.global.mbarrier::complete_tx::bytes.L2::cache_hint [%0], [%1, {%3, %4}], [%2], %5;"
                 :: "r"(dst), "l"(tm), "r"(bar), "r"(c0), "r"(c1), "l"(pol) : "memory");
}
__device__ __forceinline__ void bulk_prefetch_l2(const void* src, uint32_t bytes) {
    asm volatile("cp.async.bulk.prefetch.L2.global [%0], %1;" :: "l"(src), "r"(bytes) : "memory");
}
__device__ __forceinline__ float ex2(float x) { float y; asm("ex2.approx.ftz.f32 %0, %1;" : "=f"(y) : "f"(x)); return y; }
__device__ __forceinline__ void cp_async16_hint(uint32_t dst, const void* src, uint64_t pol) {
    asm volatile("cp.async.cg.shared.global.L2::cache_hint [%0], [%1], 16, %2;" :: "r"(dst), "l"(src), "l"(pol) : "memory");
}
__device__ __forceinline__ void cp_async_wait_all() { asm volatile("cp.async.wait_all;" ::: "memory"); }
__device__ __forceinline__ void cp_async_commit() { asm volatile("cp.async.commit_group;" ::: "memory"); }
template <int N> __device__ __forceinline__ void cp_async_wait_group() { asm volatile("cp.async.wait_group %0;" :: "n"(N) : "memory"); }

__device__ __forceinline__ void ldg128_hint(uint32_t (&r)[4], const void* p, uint64_t pol) {
    asm volatile("ld.global.nc.L1::no_allocate.L2::cache_hint.v4.u32 {%0,%1,%2,%3}, [%4], %5;"
                 : "=r"(r[0]), "=r"(r[1]), "=r"(r[2]), "=r"(r[3]) : "l"(p), "l"(pol));
}
__device__ __forceinline__ void mma16816(float (&c)[4], uint32_t a0, uint32_t a1, uint32_t a2, uint32_t a3,
                                         uint32_t b0, uint32_t b1) {
    asm volatile("mma.sync.aligned.m16n8k16.row.col.f32.bf16.bf16.f32 {%0,%1,%2,%3}, {%4,%5,%6,%7}, {%8,%9}, {%0,%1,%2,%3};"
                 : "+f"(c[0]), "+f"(c[1]), "+f"(c[2]), "+f"(c[3])
                 : "r"(a0), "r"(a1), "r"(a2), "r"(a3), "r"(b0), "r"(b1));
}
__device__ __forceinline__ void ldmatrix4(uint32_t (&r)[4], uint32_t addr) {
    asm volatile("ldmatrix.sync.aligned.m8n8.x4.shared.b16 {%0,%1,%2,%3}, [%4];"
                 : "=r"(r[0]), "=r"(r[1]), "=r"(r[2]), "=r"(r[3]) : "r"(addr) : "memory");
}
__device__ __forceinline__ void red_add_v4(float* p, float a, float b, float c, float d) {
    asm volatile("red.global.add.v4.f32 [%0], {%1,%2,%3,%4};" :: "l"(p), "f"(a), "f"(b), "f"(c), "f"(d) : "memory");
}
__device__ __forceinline__ unsigned ld_acquire(const unsigned* p) {
    unsigned v; asm volatile("ld.acquire.gpu.global.u32 %0, [%1];" : "=r"(v) : "l"(p) : "memory"); return v;
}
__device__ __forceinline__ uint32_t mapa(uint32_t addr, uint32_t rank) {
    uint32_t r; asm volatile("mapa.shared::cluster.u32 %0, %1, %2;" : "=r"(r) : "r"(addr), "r"(rank)); return r;
}
__device__ __forceinline__ void st_async_b32(uint32_t addr, uint32_t v, uint32_t bar) {
    asm volatile("st.async.weak.shared::cluster.mbarrier::complete_tx::bytes.b32 [%0], %1, [%2];" :: "r"(addr), "r"(v), "r"(bar) : "memory");
}
__device__ __forceinline__ float warp_sum(float v) {
#pragma unroll
    for (int o = 16; o > 0; o >>= 1) v += __shfl_xor_sync(0xffffffffu, v, o);
    return v;
}

__device__ __forceinline__ void grid_barrier(unsigned target) {
    __syncthreads();
    if (threadIdx.x == 0) {
        __threadfence();
        atomicAdd(&g_ctr, 1u);
        unsigned it = 0;
        while ((int)(ld_acquire(&g_ctr) - target) < 0) { if (++it > SPIN_LIMIT) __trap(); }
    }
    __syncthreads();
}

constexpr float LOG2E = 1.4426950408889634f;

__device__ __forceinline__ void ldmatrix4t(uint32_t (&r)[4], uint32_t addr) {
    asm volatile("ldmatrix.sync.aligned.m8n8.x4.trans.shared.b16 {%0,%1,%2,%3}, [%4];"
                 : "=r"(r[0]), "=r"(r[1]), "=r"(r[2]), "=r"(r[3]) : "r"(addr) : "memory");
}
__device__ __forceinline__ uint32_t pack_bf16(float lo, float hi) {
    uint32_t r; asm("cvt.rn.bf16x2.f32 %0, %1, %2;" : "=r"(r) : "f"(hi), "f"(lo)); return r;
}

__global__ void __launch_bounds__(NT, 1) fused_kernel(const Params P, const __grid_constant__ CUtensorMap tm_wq,
                                                        const __grid_constant__ CUtensorMap tm_wo,
                                                        const __grid_constant__ CUtensorMap tm_v) {
    extern __shared__ __align__(1024) unsigned char sm[];
    const int tid = threadIdx.x, lane = tid & 31, w = tid >> 5;
    const int g = lane >> 2, t = lane & 3;
    const int b = blockIdx.x, h = b >> 2, c = b & 3, r = b & 1;
    const uint32_t sbase = smem_u32(sm);
    bf16* xs = reinterpret_cast<bf16*>(sm + OFF_XS);
    bf16* xn = reinterpret_cast<bf16*>(sm + OFF_XN);
    bf16* b2s = reinterpret_cast<bf16*>(sm + OFF_B2);
    float* oscr = reinterpret_cast<float*>(sm + OFF_O);
    bf16* qs = reinterpret_cast<bf16*>(sm + OFF_Q);
    float* oex = reinterpret_cast<float*>(sm + OFF_OEX);
    float* stat = reinterpret_cast<float*>(sm + OFF_STAT);
    float* red = reinterpret_cast<float*>(sm + OFF_RED);
    bf16* hs = reinterpret_cast<bf16*>(sm + OFF_HS);
    volatile unsigned* s_flag = reinterpret_cast<volatile unsigned*>(sm + OFF_STAT + 64);
    const uint32_t bar_stage = sbase + OFF_STAT + 72;
    if (tid < D_MODEL / 8) *reinterpret_cast<uint4*>(xs + tid * 8) = __ldg(reinterpret_cast<const uint4*>(P.x) + tid);
    else if (tid < D_MODEL / 4) *reinterpret_cast<uint4*>(b2s + (tid - 80) * 8) = __ldg(reinterpret_cast<const uint4*>(P.b2) + (tid - 80));
    else if (tid < 162) { if (b < MLP_CTAS) *reinterpret_cast<uint4*>(hs + 16 + (tid - 160) * 8) = __ldg(reinterpret_cast<const uint4*>(P.b1 + b * MLP_UNITS) + (tid - 160)); }
    else if (tid == 192) s_flag[0] = ld_acquire(&g_ctr) >> 9;
    uint64_t pol_first;
    asm volatile("createpolicy.fractional.L2::evict_first.b64 %0, 1.0;" : "=l"(pol_first));
    uint64_t pol_norm;
    asm volatile("createpolicy.fractional.L2::evict_normal.b64 %0, 1.0;" : "=l"(pol_norm));

    const size_t kv_off = (size_t)(h * SEQ + c * 1024 + w * 128) * DH;
    if (tid == 224) {
        mbar_init(bar_stage, 1);
        mbar_init(sbase + OFF_XBAR, 1);
        mbar_init(sbase + OFF_XBAR + 8, 1);
        asm volatile("fence.mbarrier_init.release.cluster;" ::: "memory");
        asm volatile("fence.proxy.async.shared::cta;" ::: "memory");
        mbar_expect_tx(bar_stage, 81920);
#pragma unroll
        for (int i = 0; i < 5; i++) tma_2d_hint(sbase + OFF_STAGE + i * 16384, &tm_wq, h * DH + r * 64, i * 128, bar_stage, pol_first);
    }
    const uint32_t kb = sbase + OFF_K + w * (KSM_TILES * 16 * 256);
    {
        const bf16* kq = P.kc + kv_off + KREG_TILES * 16 * DH;
#pragma unroll 1
        for (int it = 0; it < KSM_TILES * 8; it++) {
            const int idx = it * 32 + lane;
            const int row = idx >> 4, ch = idx & 15;
            cp_async16_hint(kb + row * 256 + ((ch ^ (row & 7)) << 4), kq + row * DH + ch * 8, pol_first);
        }
    }
    cp_async_commit();
    if (b == 1) for (int e = tid; e < 3 * NREP * D_MODEL; e += NT) (&g_acc[1][0][0])[e] = 0.f;
    uint32_t kreg[KREG_TILES][2][4][4];
    __syncthreads();
    asm volatile("barrier.cluster.arrive.relaxed.aligned;" ::: "memory");
    const unsigned epoch = s_flag[0];
    const unsigned base = epoch << 9;

#pragma unroll 1
    for (int s = 0; s < 4; s++) {
        {
            float v[4] = {0.f, 0.f, 0.f, 0.f};
            if (tid < D_MODEL / 4) {
                const uint2 xr = *reinterpret_cast<const uint2*>(xs + tid * 4);
                v[0] = bflo(xr.x); v[1] = bfhi(xr.x); v[2] = bflo(xr.y); v[3] = bfhi(xr.y);
                if (s != 0) {
                    float4 a = __ldcg(reinterpret_cast<const float4*>(&g_acc[s - 1][0][0]) + tid);
#pragma unroll
                    for (int i = 1; i < NREP; i++) {
                        const float4 a2 = __ldcg(reinterpret_cast<const float4*>(&g_acc[s - 1][i][0]) + tid);
                        a.x += a2.x; a.y += a2.y; a.z += a2.z; a.w += a2.w;
                    }
                    a.x = bf16r(a.x); a.y = bf16r(a.y); a.z = bf16r(a.z); a.w = bf16r(a.w);
                    if (s == 2) {
                        const uint2 br = *reinterpret_cast<const uint2*>(b2s + tid * 4);
                        a.x = bf16r(a.x + bflo(br.x)); a.y = bf16r(a.y + bfhi(br.x));
                        a.z = bf16r(a.z + bflo(br.y)); a.w = bf16r(a.w + bfhi(br.y));
                    }
                    v[0] = bf16r(v[0] + a.x); v[1] = bf16r(v[1] + a.y); v[2] = bf16r(v[2] + a.z); v[3] = bf16r(v[3] + a.w);
                    *reinterpret_cast<uint2*>(xs + tid * 4) = make_uint2(pack_bf16(v[0], v[1]), pack_bf16(v[2], v[3]));
                }
            }
            if (s == 2 && b == 0) {
                for (int e = tid; e < NREP * D_MODEL; e += NT) (&g_acc[0][0][0])[e] = 0.f;
            }
#pragma unroll 1
            for (int rep = 0; rep <= (s & 1); rep++) {
                float mean = 0.25f * ((v[0] + v[1]) + (v[2] + v[3]));
                float m2 = (v[0] - mean) * (v[0] - mean) + (v[1] - mean) * (v[1] - mean) +
                           (v[2] - mean) * (v[2] - mean) + (v[3] - mean) * (v[3] - mean);
                float hn = 2.f;
#pragma unroll
                for (int o = 1; o < 32; o <<= 1) {
                    const float mo = __shfl_xor_sync(0xffffffffu, mean, o);
                    const float qo = __shfl_xor_sync(0xffffffffu, m2, o);
                    const float d = mo - mean;
                    m2 = m2 + qo + d * d * hn;
                    mean = 0.5f * (mean + mo);
                    hn *= 2.f;
                }
                float* rd = red + rep * 12;
                if (lane == 0 && w < 5) { rd[2 * w] = mean; rd[2 * w + 1] = m2; }
                __syncthreads();
                float gm = 0.f, gq = 0.f;
#pragma unroll
                for (int i = 0; i < 5; i++) { gm += rd[2 * i]; gq += rd[2 * i + 1]; }
                gm *= 0.2f;
#pragma unroll
                for (int i = 0; i < 5; i++) { const float d = rd[2 * i] - gm; gq += 128.f * d * d; }
                const float mb = bf16r(gm);
                const float den = bf16r(sqrtf(bf16r(bf16r(gq * (1.0f / D_MODEL)) + 1e-5f)));
#pragma unroll
                for (int i = 0; i < 4; i++) v[i] = bf16r(__fdividef(bf16r(v[i] - mb), den));
            }
            if (tid < D_MODEL / 4)
                *reinterpret_cast<uint2*>(xn + tid * 4) = make_uint2(pack_bf16(v[0], v[1]), pack_bf16(v[2], v[3]));
        }
        if (s == 1) cp_async_wait_all();
        __syncthreads();
        float* acc = &g_acc[s][b & (NREP - 1)][0];

        if (!(s & 1)) {
            const int pass = s >> 1;
            mbar_wait(bar_stage, pass);
            {
                float cq[4][4];
#pragma unroll
                for (int i = 0; i < 4; i++) { cq[i][0] = cq[i][1] = cq[i][2] = cq[i][3] = 0.f; }
#pragma unroll
                for (int k5 = 0; k5 < 5; k5++) {
                    const int ks = w * 5 + k5;
                    const uint32_t b0 = *reinterpret_cast<const uint32_t*>(xn + ks * 16 + 2 * t);
                    const uint32_t b1 = *reinterpret_cast<const uint32_t*>(xn + ks * 16 + 2 * t + 8);
                    const int krow = ks * 16 + (lane & 7) + ((lane >> 4) & 1) * 8;
#pragma unroll
                    for (int mt = 0; mt < 4; mt++) {
                        uint32_t a[4];
                        ldmatrix4t(a, sbase + OFF_STAGE + krow * 128 + (((2 * mt + ((lane >> 3) & 1)) ^ (lane & 7)) << 4));
                        mma16816(cq[mt], a[0], a[1], a[2], a[3], b0, b1);
                    }
                }
                if (t == 0) {
#pragma unroll
                    for (int mt = 0; mt < 4; mt++) { oscr[w * 64 + mt * 16 + g] = cq[mt][0]; oscr[w * 64 + mt * 16 + 8 + g] = cq[mt][2]; }
                }
            }
            __syncthreads();
            if (s == 0) asm volatile("barrier.cluster.wait.aligned;" ::: "memory");
            if (tid < 32) {
                float s0 = 0.f, s1 = 0.f;
#pragma unroll
                for (int i = 0; i < 8; i++) { const float2 v2 = *reinterpret_cast<const float2*>(oscr + i * 64 + 2 * tid); s0 += v2.x; s1 += v2.y; }
                const uint32_t qp = pack_bf16(s0, s1);
                *reinterpret_cast<uint32_t*>(qs + r * 64 + 2 * tid) = qp;
                st_async_b32(mapa(sbase + OFF_Q + (r * 64 + 2 * tid) * 2, r ^ 1), qp, mapa(sbase + OFF_XBAR, r ^ 1));
                if (tid == 0) { mbar_expect_tx(sbase + OFF_XBAR, 128); mbar_expect_tx(sbase + OFF_XBAR + 8, 256); }
            }
            const uint32_t vland = sbase + OFF_STAGE + w * (VL * 4096);
            if (tid == 224) {
                mbar_expect_tx(bar_stage, 8 * VL * 4096);
#pragma unroll 1
                for (int i = 0; i < 16; i++)
                    tma_2d_hint(sbase + OFF_STAGE + i * (VL * 2048), &tm_v, (i & 1) * 64, h * SEQ + c * 1024 + (i >> 1) * 128, bar_stage, pol_first);
            }
            if (s == 0) {
                const bf16* kp = P.kc + kv_off + (g * DH + t * 8);
#pragma unroll
                for (int i = 0; i < KREG_TILES; i++)
#pragma unroll
                    for (int hh = 0; hh < 2; hh++)
#pragma unroll
                        for (int j = 0; j < 4; j++)
                            ldg128_hint(kreg[i][hh][j], kp + (i * 16 + hh * 8) * DH + j * 32, pol_first);
            }
            __syncthreads();
            mbar_wait(sbase + OFF_XBAR, pass);

            float sc[8][2];
            {
                float cacc[KREG_TILES][4];
#pragma unroll
                for (int i = 0; i < KREG_TILES; i++) { cacc[i][0] = cacc[i][1] = cacc[i][2] = cacc[i][3] = 0.f; }
#pragma unroll
                for (int j = 0; j < 4; j++) {
                    const uint4 qv = *reinterpret_cast<const uint4*>(qs + j * 32 + t * 8);
#pragma unroll
                    for (int i = 0; i < KREG_TILES; i++) {
                        mma16816(cacc[i], kreg[i][0][j][0], kreg[i][1][j][0], kreg[i][0][j][1], kreg[i][1][j][1], qv.x, qv.y);
                        mma16816(cacc[i], kreg[i][0][j][2], kreg[i][1][j][2], kreg[i][0][j][3], kreg[i][1][j][3], qv.z, qv.w);
                    }
                }
#pragma unroll
                for (int i = 0; i < KREG_TILES; i++) { sc[i][0] = cacc[i][0]; sc[i][1] = cacc[i][2]; }
            }
            {
                if (s == 0) {
                    if (lane == 0) bulk_prefetch_l2(P.vc + kv_off + VL * 16 * DH, (8 - VL) * 4096);
                    cp_async_wait_all();
                    __syncwarp();
                }
                float cacc[KSM_TILES][4];
#pragma unroll
                for (int tt = 0; tt < KSM_TILES; tt++) { cacc[tt][0] = cacc[tt][1] = cacc[tt][2] = cacc[tt][3] = 0.f; }
                const int row0 = (lane & 7) + ((lane >> 3) & 1) * 8;
#pragma unroll 4
                for (int ks = 0; ks < 8; ks++) {
                    const uint32_t b0 = *reinterpret_cast<const uint32_t*>(qs + ks * 16 + 2 * t);
                    const uint32_t b1 = *reinterpret_cast<const uint32_t*>(qs + ks * 16 + 2 * t + 8);
                    const int ch = 2 * ks + (lane >> 4);
                    const uint32_t ad = kb + row0 * 256 + ((ch ^ (lane & 7)) << 4);
#pragma unroll
                    for (int tt = 0; tt < KSM_TILES; tt++) {
                        uint32_t a[4];
                        ldmatrix4(a, ad + tt * 4096);
                        mma16816(cacc[tt], a[0], a[1], a[2], a[3], b0, b1);
                    }
                }
#pragma unroll
                for (int tt = 0; tt < KSM_TILES; tt++) { sc[KREG_TILES + tt][0] = cacc[tt][0]; sc[KREG_TILES + tt][1] = cacc[tt][2]; }
            }
            bf16* pw = reinterpret_cast<bf16*>(sm + OFF_P + w * 256);
            {
                float s4[4];
#pragma unroll
                for (int q2 = 0; q2 < 4; q2++) {
                    const int i = q2 >> 1, k2 = q2 & 1;
                    const float v01 = (t & 1) ? sc[2 + i][k2] : sc[i][k2];
                    const float v23 = (t & 1) ? sc[6 + i][k2] : sc[4 + i][k2];
                    s4[q2] = (t & 2) ? v23 : v01;
                }
                float mx = -INFINITY;
#pragma unroll
                for (int q2 = 0; q2 < 4; q2++) {
                    s4[q2] = bf16r(bf16r(s4[q2]) * 0.08838834764831845f);
                    mx = fmaxf(mx, s4[q2]);
                }
#pragma unroll
                for (int o = 1; o < 32; o <<= 1) mx = fmaxf(mx, __shfl_xor_sync(0xffffffffu, mx, o));
                float l = 0.f;
#pragma unroll
                for (int q2 = 0; q2 < 4; q2++) {
                    const bf16 pb = __float2bfloat16_rn(ex2((s4[q2] - mx) * LOG2E));
                    l += __bfloat162float(pb);
                    pw[(2 * t + (q2 >> 1)) * 16 + (q2 & 1) * 8 + g] = pb;
                }
                l = warp_sum(l);
                if (lane == 0) { stat[2 * w] = mx; stat[2 * w + 1] = l; }
            }
            __syncthreads();
            float m_cta = stat[0];
#pragma unroll
            for (int i = 1; i < 8; i++) m_cta = fmaxf(m_cta, stat[2 * i]);
            const float wfac = ex2((stat[2 * w] - m_cta) * LOG2E);
            if (tid == 0) {
                float l_cta = 0.f;
#pragma unroll
                for (int i = 0; i < 8; i++) l_cta += stat[2 * i + 1] * ex2((stat[2 * i] - m_cta) * LOG2E);
                asm volatile("st.relaxed.gpu.global.v4.u32 [%0], {%1,%2,%3,%4};" :: "l"(&g_ml[pass][b]),
                             "r"(__float_as_uint(m_cta)), "r"(__float_as_uint(l_cta)), "r"(epoch * 2 + pass + 1), "r"(0u) : "memory");
            }

            {
                const bf16* vbase = P.vc + kv_off + (4 * t) * DH + g * 8;
                float* ow = oscr + w * 128;
                constexpr int NK = 8 - VL;
                static_assert(NK % NVB == 0, "NVB");
                uint32_t vbuf[NVB][4][4];
#pragma unroll
                for (int u = 0; u < NVB - 1; u++)
#pragma unroll
                    for (int i = 0; i < 4; i++) ldg128_hint(vbuf[u][i], vbase + ((VL + u) * 16 + i) * DH, pol_norm);
                mbar_wait(bar_stage, pass ^ 1);
#pragma unroll 4
                for (int mt = 0; mt < 8; mt++) {
                    float cl[4] = {0.f, 0.f, 0.f, 0.f};
#pragma unroll
                    for (int kt = 0; kt < VL; kt++) {
                        const uint32_t b0 = *reinterpret_cast<const uint32_t*>(pw + kt * 16 + 2 * t);
                        const uint32_t b1 = *reinterpret_cast<const uint32_t*>(pw + kt * 16 + 2 * t + 8);
                        const int row = kt * 16 + (lane & 7) + ((lane >> 4) & 1) * 8;
                        uint32_t a[4];
                        ldmatrix4t(a, vland + (mt >> 2) * (VL * 2048) + row * 128 + ((((2 * mt + ((lane >> 3) & 1)) ^ lane) & 7) << 4));
                        mma16816(cl, a[0], a[1], a[2], a[3], b0, b1);
                    }
                    if (t == 0) { ow[mt * 16 + g] = cl[0] * wfac; ow[mt * 16 + 8 + g] = cl[2] * wfac; }
                }
                __syncwarp();
                if (w != 7) asm volatile("bar.arrive 1, 256;" ::: "memory");
                float oacc[4][4];
#pragma unroll
                for (int i = 0; i < 4; i++) { oacc[i][0] = oacc[i][1] = oacc[i][2] = oacc[i][3] = 0.f; }
#pragma unroll 1
                for (int hf = 0; hf < 2; hf++) {
#pragma unroll 1
                    for (int k0 = 0; k0 < NK; k0 += NVB) {
                        if (w == 7 && hf == 1 && k0 == 2) {
                            asm volatile("bar.sync 1, 256;" ::: "memory");
                            if (lane == 0) {
                                mbar_expect_tx(bar_stage, 81920);
#pragma unroll 1
                                for (int i = 0; i < 10; i++) tma_2d_hint(sbase + OFF_STAGE + i * 8192, &tm_wo, i * 64, h * DH + r * 64, bar_stage, pol_first);
                            }
                            __syncwarp();
                        }
#pragma unroll
                        for (int u = 0; u < NVB; u++) {
                            const int kt = k0 + u;
                            int nk = kt + NVB - 1, nh = hf;
                            if (nk >= NK) { nk -= NK; nh = hf + 1; }
                            if (nh < 2) {
                                const bf16* vp = vbase + (VL + nk) * 16 * DH + nh * 64;
#pragma unroll
                                for (int i = 0; i < 4; i++) ldg128_hint(vbuf[(u + NVB - 1) % NVB][i], vp + i * DH, pol_norm);
                            }
                            const uint2 pb = *reinterpret_cast<const uint2*>(pw + (VL + kt) * 16 + 4 * t);
#pragma unroll
                            for (int e = 0; e < 4; e++)
                                mma16816(oacc[e], __byte_perm(vbuf[u][0][e], vbuf[u][1][e], 0x5410), __byte_perm(vbuf[u][0][e], vbuf[u][1][e], 0x7632),
                                         __byte_perm(vbuf[u][2][e], vbuf[u][3][e], 0x5410), __byte_perm(vbuf[u][2][e], vbuf[u][3][e], 0x7632), pb.x, pb.y);
                        }
                    }
                    if (t == 0) {
                        float* o2 = ow + hf * 64 + g * 8;
                        float4 u0 = *reinterpret_cast<float4*>(o2), u1 = *reinterpret_cast<float4*>(o2 + 4);
                        u0.x += oacc[0][0] * wfac; u0.y += oacc[0][2] * wfac; u0.z += oacc[1][0] * wfac; u0.w += oacc[1][2] * wfac;
                        u1.x += oacc[2][0] * wfac; u1.y += oacc[2][2] * wfac; u1.z += oacc[3][0] * wfac; u1.w += oacc[3][2] * wfac;
                        *reinterpret_cast<float4*>(o2) = u0;
                        *reinterpret_cast<float4*>(o2 + 4) = u1;
                    }
#pragma unroll
                    for (int i = 0; i < 4; i++) { oacc[i][0] = oacc[i][1] = oacc[i][2] = oacc[i][3] = 0.f; }
                }
            }
            if (s == 0 && b < MLP_CTAS) {
#pragma unroll 1
                for (int idx = tid; idx < 2 * D_MODEL; idx += NT) {
                    const int row = idx >> 1, hf = idx & 1;
                    cp_async16_hint(sbase + OFF_W1 + row * 32 + hf * 16, P.w1 + (size_t)row * FF + b * MLP_UNITS + hf * 8, pol_first);
                    const int r2 = idx / 80, ch = idx - r2 * 80;
                    cp_async16_hint(sbase + OFF_W2 + r2 * 1280 + ((ch ^ (r2 & 7)) << 4), P.w2 + (size_t)(b * MLP_UNITS) * D_MODEL + idx * 8, pol_first);
                }
                cp_async_commit();
            }
            __syncthreads();
            if (tid < 128) {
                uint4 rec[4];
                {
                    unsigned it = 0;
                    const unsigned tag = epoch * 2 + pass + 1;
                    while (true) {
#pragma unroll
                        for (int i = 0; i < 4; i++)
                            asm volatile("ld.relaxed.gpu.global.v4.u32 {%0,%1,%2,%3}, [%4];"
                                         : "=r"(rec[i].x), "=r"(rec[i].y), "=r"(rec[i].z), "=r"(rec[i].w)
                                         : "l"(&g_ml[pass][(b & ~3) + i]) : "memory");
                        if (rec[0].z == tag && rec[1].z == tag && rec[2].z == tag && rec[3].z == tag) break;
                        if (++it > SPIN_LIMIT) __trap();
                    }
                }
                const float M = fmaxf(fmaxf(__uint_as_float(rec[0].x), __uint_as_float(rec[1].x)),
                                      fmaxf(__uint_as_float(rec[2].x), __uint_as_float(rec[3].x)));
                float L = 0.f;
#pragma unroll
                for (int i = 0; i < 4; i++) L += __uint_as_float(rec[i].y) * ex2((__uint_as_float(rec[i].x) - M) * LOG2E);
                const float scale = __fdividef(ex2((m_cta - M) * LOG2E), L);
                float sum = 0.f;
#pragma unroll
                for (int i = 0; i < 8; i++) sum += oscr[i * 128 + tid];
                if ((tid >> 6) == r) oex[r * 64 + (tid & 63)] = sum * scale;
                else st_async_b32(mapa(sbase + OFF_OEX + (r * 64 + (tid & 63)) * 4, r ^ 1), __float_as_uint(sum * scale), mapa(sbase + OFF_XBAR + 8, r ^ 1));
            }
            __syncthreads();
            if (tid < 64) {
                mbar_wait(sbase + OFF_XBAR + 8, pass);
                const float o = oex[tid] + oex[64 + tid];
                const bf16 hi = __float2bfloat16_rn(o);
                hs[32 + tid] = hi;
                hs[96 + tid] = __float2bfloat16_rn(o - __bfloat162float(hi));
            }
            mbar_wait(bar_stage, pass);
            __syncthreads();
            {
                float co[5][4];
#pragma unroll
                for (int i = 0; i < 5; i++) { co[i][0] = co[i][1] = co[i][2] = co[i][3] = 0.f; }
#pragma unroll 1
                for (int ks = 0; ks < 4; ks++) {
                    uint32_t b0 = 0, b1 = 0;
                    if (g < 2) {
                        b0 = *reinterpret_cast<const uint32_t*>(hs + 32 + g * 64 + ks * 16 + 2 * t);
                        b1 = *reinterpret_cast<const uint32_t*>(hs + 32 + g * 64 + ks * 16 + 2 * t + 8);
                    }
                    const int krow = ks * 16 + (lane & 7) + ((lane >> 4) & 1) * 8;
#pragma unroll
                    for (int i = 0; i < 5; i++) {
                        const int ch = 2 * (w * 5 + i) + ((lane >> 3) & 1);
                        uint32_t a[4];
                        ldmatrix4t(a, sbase + OFF_STAGE + (ch >> 3) * 8192 + krow * 128 + (((ch ^ lane) & 7) << 4));
                        mma16816(co[i], a[0], a[1], a[2], a[3], b0, b1);
                    }
                }
                if (t == 0) {
#pragma unroll
                    for (int i = 0; i < 5; i++) {
                        oscr[(w * 5 + i) * 16 + g] = co[i][0] + co[i][1];
                        oscr[(w * 5 + i) * 16 + 8 + g] = co[i][2] + co[i][3];
                    }
                }
                __syncwarp();
                if (lane < 20) {
                    const float4 v4 = *reinterpret_cast<const float4*>(oscr + w * 80 + lane * 4);
                    red_add_v4(acc + w * 80 + lane * 4, v4.x, v4.y, v4.z, v4.w);
                }
            }
            if (s == 0) {
                __syncthreads();
                if (tid == 224) {
                    mbar_expect_tx(bar_stage, 81920);
#pragma unroll 1
                    for (int i = 0; i < 5; i++) tma_2d_hint(sbase + OFF_STAGE + i * 16384, &tm_wq, h * DH + r * 64, i * 128, bar_stage, pol_first);
                }
            }
        } else if (b < MLP_CTAS) {
            {
                float ch4[4] = {0.f, 0.f, 0.f, 0.f};
#pragma unroll
                for (int k5 = 0; k5 < 5; k5++) {
                    const int ks = w * 5 + k5;
                    const uint32_t b0 = *reinterpret_cast<const uint32_t*>(xn + ks * 16 + 2 * t);
                    const uint32_t b1 = *reinterpret_cast<const uint32_t*>(xn + ks * 16 + 2 * t + 8);
                    const int krow = ks * 16 + (lane & 7) + ((lane >> 4) & 1) * 8;
                    uint32_t a[4];
                    ldmatrix4t(a, sbase + OFF_W1 + krow * 32 + ((lane >> 3) & 1) * 16);
                    mma16816(ch4, a[0], a[1], a[2], a[3], b0, b1);
                }
                if (t == 0) { oscr[w * 16 + g] = ch4[0]; oscr[w * 16 + 8 + g] = ch4[2]; }
            }
            __syncthreads();
            if (tid < 16) {
                float sum = 0.f;
#pragma unroll
                for (int i = 0; i < 8; i++) sum += oscr[i * 16 + tid];
                const float u = bf16r(bf16r(sum) + __bfloat162float(hs[16 + tid]));
                const float inner = 0.7978845608028654f * (u + 0.044715f * u * u * u);
                const float th = 1.0f - __fdividef(2.0f, ex2(inner * (2.0f * LOG2E)) + 1.0f);
                hs[tid] = __float2bfloat16_rn(0.5f * u * (1.0f + th));
            }
            __syncthreads();
            {
                const uint32_t b0 = *reinterpret_cast<const uint32_t*>(hs + 2 * t);
                const uint32_t b1 = *reinterpret_cast<const uint32_t*>(hs + 2 * t + 8);
                const int krow = (lane & 7) + ((lane >> 4) & 1) * 8;
#pragma unroll
                for (int i = 0; i < 5; i++) {
                    const int ch = 2 * (w * 5 + i) + ((lane >> 3) & 1);
                    uint32_t a[4];
                    float co[4] = {0.f, 0.f, 0.f, 0.f};
                    ldmatrix4t(a, sbase + OFF_W2 + krow * 1280 + ((ch ^ (lane & 7)) << 4));
                    mma16816(co, a[0], a[1], a[2], a[3], b0, b1);
                    if (t == 0) {
                        oscr[256 + (w * 5 + i) * 16 + g] = co[0];
                        oscr[256 + (w * 5 + i) * 16 + 8 + g] = co[2];
                    }
                }
                __syncwarp();
                if (lane < 20) {
                    const float4 v4 = *reinterpret_cast<const float4*>(oscr + 256 + w * 80 + lane * 4);
                    red_add_v4(acc + w * 80 + lane * 4, v4.x, v4.y, v4.z, v4.w);
                }
            }
        }
        if (s < 3) grid_barrier(base + NCTA * (s + 1));
    }
    __syncthreads();
    if (tid == 0) {
        __threadfence();
        const unsigned old = atomicAdd(&g_ctr, 1u);
        s_flag[1] = (old == base + 4 * NCTA - 1) ? 1u : 0u;
        __threadfence();
    }
    __syncthreads();
    if (s_flag[1]) {
        for (int e = tid; e < D_MODEL; e += NT) {
            float a = 0.f;
#pragma unroll
            for (int i = 0; i < NREP; i++) a += __ldcg(&g_acc[3][i][e]);
            const float o = bf16r(bf16r(a) + __bfloat162float(b2s[e]));
            P.out[e] = __float2bfloat16_rn(__bfloat162float(xs[e]) + o);
        }
    }
}

}

extern "C" void kernel_launch(void* const* d_in, const int* in_sizes, int n_in,
                              void* d_out, int out_size) {
    Params P;
    P.x = (const bf16*)d_in[0];
    P.kc = (const bf16*)d_in[1];
    P.vc = (const bf16*)d_in[2];
    P.wq = (const bf16*)d_in[3];
    P.wo = (const bf16*)d_in[4];
    P.w1 = (const bf16*)d_in[6];
    P.b1 = (const bf16*)d_in[7];
    P.w2 = (const bf16*)d_in[8];
    P.b2 = (const bf16*)d_in[9];
    P.out = (bf16*)d_out;

    cudaFuncSetAttribute(fused_kernel, cudaFuncAttributeMaxDynamicSharedMemorySize, SMEM_BYTES);

    typedef CUresult (*EncodeFn)(CUtensorMap*, CUtensorMapDataType, cuuint32_t, void*, const cuuint64_t*, const cuuint64_t*,
                                 const cuuint32_t*, const cuuint32_t*, CUtensorMapInterleave, CUtensorMapSwizzle,
                                 CUtensorMapL2promotion, CUtensorMapFloatOOBfill);
    void* fn = nullptr;
    cudaDriverEntryPointQueryResult qres;
    cudaGetDriverEntryPoint("cuTensorMapEncodeTiled", &fn, cudaEnableDefault, &qres);
    EncodeFn encode = (EncodeFn)fn;
    CUtensorMap tm_wq, tm_wo, tm_v;
    {
        cuuint64_t dims[2] = {(cuuint64_t)(NHEAD * DH), (cuuint64_t)D_MODEL};
        cuuint64_t strides[1] = {(cuuint64_t)(NHEAD * DH * 2)};
        cuuint32_t box[2] = {64, 128};
        cuuint32_t es[2] = {1, 1};
        encode(&tm_wq, CU_TENSOR_MAP_DATA_TYPE_BFLOAT16, 2, (void*)P.wq, dims, strides, box, es, CU_TENSOR_MAP_INTERLEAVE_NONE,
               CU_TENSOR_MAP_SWIZZLE_128B, CU_TENSOR_MAP_L2_PROMOTION_NONE, CU_TENSOR_MAP_FLOAT_OOB_FILL_NONE);
    }
    {
        cuuint64_t dims[2] = {(cuuint64_t)D_MODEL, (cuuint64_t)(NHEAD * DH)};
        cuuint64_t strides[1] = {(cuuint64_t)(D_MODEL * 2)};
        cuuint32_t box[2] = {64, 64};
        cuuint32_t es[2] = {1, 1};
        encode(&tm_wo, CU_TENSOR_MAP_DATA_TYPE_BFLOAT16, 2, (void*)P.wo, dims, strides, box, es, CU_TENSOR_MAP_INTERLEAVE_NONE,
               CU_TENSOR_MAP_SWIZZLE_128B, CU_TENSOR_MAP_L2_PROMOTION_NONE, CU_TENSOR_MAP_FLOAT_OOB_FILL_NONE);
    }

    {
        cuuint64_t dims[2] = {(cuuint64_t)DH, (cuuint64_t)(NHEAD * SEQ)};
        cuuint64_t strides[1] = {(cuuint64_t)(DH * 2)};
        cuuint32_t box[2] = {64, VL * 16};
        cuuint32_t es[2] = {1, 1};
        encode(&tm_v, CU_TENSOR_MAP_DATA_TYPE_BFLOAT16, 2, (void*)P.vc, dims, strides, box, es, CU_TENSOR_MAP_INTERLEAVE_NONE,
               CU_TENSOR_MAP_SWIZZLE_128B, CU_TENSOR_MAP_L2_PROMOTION_NONE, CU_TENSOR_MAP_FLOAT_OOB_FILL_NONE);
    }
    cudaLaunchConfig_t cfg = {};
    cfg.gridDim = dim3(NCTA);
    cfg.blockDim = dim3(NT);
    cfg.dynamicSmemBytes = SMEM_BYTES;
    cfg.stream = cudaStreamPerThread;
    cudaLaunchAttribute at[2];
    at[0].id = cudaLaunchAttributeClusterDimension;
    at[0].val.clusterDim.x = 2; at[0].val.clusterDim.y = 1; at[0].val.clusterDim.z = 1;
    at[1].id = cudaLaunchAttributeCooperative;
    at[1].val.cooperative = 1;
    cfg.attrs = at;
    cfg.numAttrs = 2;
    cudaLaunchKernelEx(&cfg, fused_kernel, P, tm_wq, tm_wo, tm_v);
}
```

```cpp
#include <cuda_runtime.h>
#include <cuda.h>
#include <cuda_bf16.h>
#include <stdint.h>

typedef __nv_bfloat16 bf16;

namespace {

constexpr int D_MODEL = 640;
constexpr int NHEAD = 32;
constexpr int SEQ = 4096;
constexpr int DH = 128;
constexpr int FF = 1728;
constexpr int NCTA = 128;
constexpr int NT = 256;
constexpr int KREG_TILES = 5;
constexpr int KSM_TILES = 3;
constexpr int MLP_UNITS = 16;
constexpr int MLP_CTAS = FF / MLP_UNITS;

constexpr int OFF_STAGE = 0;
constexpr int OFF_W2 = 81920;
constexpr int OFF_W1 = OFF_W2 + 20480;
constexpr int OFF_K = OFF_W1 + 20480;
constexpr int OFF_XS = OFF_K + 98304;
constexpr int OFF_XN = OFF_XS + 1280;
constexpr int OFF_O = OFF_XN + 1280;
constexpr int OFF_P = OFF_O + 4096;
constexpr int OFF_Q = OFF_P + 2048;
constexpr int OFF_OEX = OFF_Q + 256;
constexpr int OFF_STAT = OFF_OEX + 512;
constexpr int OFF_RED = OFF_STAT + 80;
constexpr int OFF_HS = OFF_RED + 96;
constexpr int OFF_B2 = OFF_HS + 320;
constexpr int OFF_XBAR = OFF_B2 + 1280;
constexpr int SMEM_BYTES = OFF_XBAR + 16;

static_assert(SMEM_BYTES <= 232448, "smem");
constexpr int NREP = 8;
constexpr int VL = 2;
constexpr int NVB = 2;
constexpr unsigned SPIN_LIMIT = 1u << 24;

__device__ unsigned int g_ctr;
__device__ float g_acc[4][NREP][D_MODEL];
__device__ uint4 g_ml[2][NCTA];

struct Params {
    const bf16* x; const bf16* kc; const bf16* vc; const bf16* wq; const bf16* wo;
    const bf16* w1; const bf16* b1; const bf16* w2; const bf16* b2; bf16* out;
};

__device__ __forceinline__ float bf16r(float x) { return __bfloat162float(__float2bfloat16_rn(x)); }
__device__ __forceinline__ float bflo(uint32_t u) { return __uint_as_float(u << 16); }
__device__ __forceinline__ float bfhi(uint32_t u) { return __uint_as_float(u & 0xffff0000u); }

__device__ __forceinline__ uint32_t smem_u32(const void* p) { return (uint32_t)__cvta_generic_to_shared(p); }

__device__ __forceinline__ void mbar_init(uint32_t bar, uint32_t cnt) {
    asm volatile("mbarrier.init.shared::cta.b64 [%0], %1;" :: "r"(bar), "r"(cnt) : "memory");
}
__device__ __forceinline__ void mbar_expect_tx(uint32_t bar, uint32_t bytes) {
    asm volatile("mbarrier.arrive.expect_tx.shared::cta.b64 _, [%0], %1;" :: "r"(bar), "r"(bytes) : "memory");
}
__device__ __forceinline__ void mbar_wait(uint32_t bar, uint32_t parity) {
    unsigned it = 0;
    while (true) {
        uint32_t ok;
        asm volatile("{\n\t.reg .pred p;\n\tmbarrier.try_wait.parity.shared::cta.b64 p, [%1], %2;\n\tselp.u32 %0, 1, 0, p;\n\t}"
                     : "=r"(ok) : "r"(bar), "r"(parity) : "memory");
        if (ok) break;
        if (++it > SPIN_LIMIT) __trap();
    }
}
__device__ __forceinline__ void tma_2d_hint(uint32_t dst, const CUtensorMap* tm, int c0, int c1, uint32_t bar, uint64_t pol) {
    asm volatile("cp.async.bulk.tensor.2d.shared::cluster.global.mbarrier::complete_tx::bytes.L2::cache_hint [%0], [%1, {%3, %4}], [%2], %5;"
                 :: "r"(dst), "l"(tm), "r"(bar), "r"(c0), "r"(c1), "l"(pol) : "memory");
}
__device__ __forceinline__ void bulk_prefetch_l2(const void* src, uint32_t bytes) {
    asm volatile("cp.async.bulk.prefetch.L2.global [%0], %1;" :: "l"(src), "r"(bytes) : "memory");
}
__device__ __forceinline__ float ex2(float x) { float y; asm("ex2.approx.ftz.f32 %0, %1;" : "=f"(y) : "f"(x)); return y; }
__device__ __forceinline__ void cp_async16_hint(uint32_t dst, const void* src, uint64_t pol) {
    asm volatile("cp.async.cg.shared.global.L2::cache_hint [%0], [%1], 16, %2;" :: "r"(dst), "l"(src), "l"(pol) : "memory");
}
__device__ __forceinline__ void cp_async_wait_all() { asm volatile("cp.async.wait_all;" ::: "memory"); }
__device__ __forceinline__ void cp_async_commit() { asm volatile("cp.async.commit_group;" ::: "memory"); }
template <int N> __device__ __forceinline__ void cp_async_wait_group() { asm volatile("cp.async.wait_group %0;" :: "n"(N) : "memory"); }

__device__ __forceinline__ void ldg128_hint(uint32_t (&r)[4], const void* p, uint64_t pol) {
    asm volatile("ld.global.nc.L1::no_allocate.L2::cache_hint.v4.u32 {%0,%1,%2,%3}, [%4], %5;"
                 : "=r"(r[0]), "=r"(r[1]), "=r"(r[2]), "=r"(r[3]) : "l"(p), "l"(pol));
}
__device__ __forceinline__ void mma16816(float (&c)[4], uint32_t a0, uint32_t a1, uint32_t a2, uint32_t a3,
                                         uint32_t b0, uint32_t b1) {
    asm volatile("mma.sync.aligned.m16n8k16.row.col.f32.bf16.bf16.f32 {%0,%1,%2,%3}, {%4,%5,%6,%7}, {%8,%9}, {%0,%1,%2,%3};"
                 : "+f"(c[0]), "+f"(c[1]), "+f"(c[2]), "+f"(c[3])
                 : "r"(a0), "r"(a1), "r"(a2), "r"(a3), "r"(b0), "r"(b1));
}
__device__ __forceinline__ void ldmatrix4(uint32_t (&r)[4], uint32_t addr) {
    asm volatile("ldmatrix.sync.aligned.m8n8.x4.shared.b16 {%0,%1,%2,%3}, [%4];"
                 : "=r"(r[0]), "=r"(r[1]), "=r"(r[2]), "=r"(r[3]) : "r"(addr) : "memory");
}
__device__ __forceinline__ void red_add_v4(float* p, float a, float b, float c, float d) {
    asm volatile("red.global.add.v4.f32 [%0], {%1,%2,%3,%4};" :: "l"(p), "f"(a), "f"(b), "f"(c), "f"(d) : "memory");
}
__device__ __forceinline__ unsigned ld_acquire(const unsigned* p) {
    unsigned v; asm volatile("ld.acquire.gpu.global.u32 %0, [%1];" : "=r"(v) : "l"(p) : "memory"); return v;
}
__device__ __forceinline__ uint32_t mapa(uint32_t addr, uint32_t rank) {
    uint32_t r; asm volatile("mapa.shared::cluster.u32 %0, %1, %2;" : "=r"(r) : "r"(addr), "r"(rank)); return r;
}
__device__ __forceinline__ void st_async_b32(uint32_t addr, uint32_t v, uint32_t bar) {
    asm volatile("st.async.weak.shared::cluster.mbarrier::complete_tx::bytes.b32 [%0], %1, [%2];" :: "r"(addr), "r"(v), "r"(bar) : "memory");
}
__device__ __forceinline__ float warp_sum(float v) {
#pragma unroll
    for (int o = 16; o > 0; o >>= 1) v += __shfl_xor_sync(0xffffffffu, v, o);
    return v;
}

__device__ __forceinline__ void grid_barrier(unsigned target) {
    __syncthreads();
    if (threadIdx.x == 0) {
        asm volatile("red.release.gpu.global.add.u32 [%0], 1;" :: "l"(&g_ctr) : "memory");
        unsigned it = 0;
        while ((int)(ld_acquire(&g_ctr) - target) < 0) { if (++it > SPIN_LIMIT) __trap(); }
    }
    __syncthreads();
}

constexpr float LOG2E = 1.4426950408889634f;

__device__ __forceinline__ void ldmatrix4t(uint32_t (&r)[4], uint32_t addr) {
    asm volatile("ldmatrix.sync.aligned.m8n8.x4.trans.shared.b16 {%0,%1,%2,%3}, [%4];"
                 : "=r"(r[0]), "=r"(r[1]), "=r"(r[2]), "=r"(r[3]) : "r"(addr) : "memory");
}
__device__ __forceinline__ uint32_t pack_bf16(float lo, float hi) {
    uint32_t r; asm("cvt.rn.bf16x2.f32 %0, %1, %2;" : "=r"(r) : "f"(hi), "f"(lo)); return r;
}

__global__ void __launch_bounds__(NT, 1) fused_kernel(const Params P, const __grid_constant__ CUtensorMap tm_wq,
                                                        const __grid_constant__ CUtensorMap tm_wo) {
    extern __shared__ __align__(1024) unsigned char sm[];
    const int tid = threadIdx.x, lane = tid & 31, w = tid >> 5;
    const int g = lane >> 2, t = lane & 3;
    const int b = blockIdx.x, h = b >> 2, c = b & 3, r = b & 1;
    const uint32_t sbase = smem_u32(sm);
    bf16* xs = reinterpret_cast<bf16*>(sm + OFF_XS);
    bf16* xn = reinterpret_cast<bf16*>(sm + OFF_XN);
    bf16* b2s = reinterpret_cast<bf16*>(sm + OFF_B2);
    float* oscr = reinterpret_cast<float*>(sm + OFF_O);
    bf16* qs = reinterpret_cast<bf16*>(sm + OFF_Q);
    float* oex = reinterpret_cast<float*>(sm + OFF_OEX);
    float* stat = reinterpret_cast<float*>(sm + OFF_STAT);
    float* red = reinterpret_cast<float*>(sm + OFF_RED);
    bf16* hs = reinterpret_cast<bf16*>(sm + OFF_HS);
    volatile unsigned* s_flag = reinterpret_cast<volatile unsigned*>(sm + OFF_STAT + 64);
    const uint32_t bar_stage = sbase + OFF_STAT + 72;
    if (tid < D_MODEL / 8) *reinterpret_cast<uint4*>(xs + tid * 8) = __ldg(reinterpret_cast<const uint4*>(P.x) + tid);
    else if (tid < D_MODEL / 4) *reinterpret_cast<uint4*>(b2s + (tid - 80) * 8) = __ldg(reinterpret_cast<const uint4*>(P.b2) + (tid - 80));
    else if (tid < 162) { if (b < MLP_CTAS) *reinterpret_cast<uint4*>(hs + 16 + (tid - 160) * 8) = __ldg(reinterpret_cast<const uint4*>(P.b1 + b * MLP_UNITS) + (tid - 160)); }
    else if (tid == 192) s_flag[0] = ld_acquire(&g_ctr) >> 9;
    uint64_t pol_first;
    asm volatile("createpolicy.fractional.L2::evict_first.b64 %0, 1.0;" : "=l"(pol_first));
    uint64_t pol_norm;
    asm volatile("createpolicy.fractional.L2::evict_normal.b64 %0, 1.0;" : "=l"(pol_norm));

    const size_t kv_off = (size_t)(h * SEQ + c * 1024 + w * 128) * DH;
    if (tid == 224) {
        mbar_init(bar_stage, 1);
        mbar_init(sbase + OFF_XBAR, 1);
        mbar_init(sbase + OFF_XBAR + 8, 1);
        asm volatile("fence.mbarrier_init.release.cluster;" ::: "memory");
        asm volatile("fence.proxy.async.shared::cta;" ::: "memory");
        mbar_expect_tx(bar_stage, 81920);
#pragma unroll
        for (int i = 0; i < 5; i++) tma_2d_hint(sbase + OFF_STAGE + i * 16384, &tm_wq, h * DH + r * 64, i * 128, bar_stage, pol_first);
    }
    const uint32_t kb = sbase + OFF_K + w * (KSM_TILES * 16 * 256);
    {
        const bf16* kq = P.kc + kv_off + KREG_TILES * 16 * DH;
#pragma unroll 1
        for (int it = 0; it < KSM_TILES * 8; it++) {
            const int idx = it * 32 + lane;
            const int row = idx >> 4, ch = idx & 15;
            cp_async16_hint(kb + row * 256 + ((ch ^ (row & 7)) << 4), kq + row * DH + ch * 8, pol_first);
        }
    }
    cp_async_commit();
    if (b == 1) for (int e = tid; e < 3 * NREP * D_MODEL; e += NT) (&g_acc[1][0][0])[e] = 0.f;
    uint32_t kreg[KREG_TILES][2][4][4];
    __syncthreads();
    asm volatile("barrier.cluster.arrive.relaxed.aligned;" ::: "memory");
    const unsigned epoch = s_flag[0];
    const unsigned base = epoch << 9;

#pragma unroll 1
    for (int s = 0; s < 4; s++) {
        {
            float v[4] = {0.f, 0.f, 0.f, 0.f};
            if (tid < D_MODEL / 4) {
                const uint2 xr = *reinterpret_cast<const uint2*>(xs + tid * 4);
                v[0] = bflo(xr.x); v[1] = bfhi(xr.x); v[2] = bflo(xr.y); v[3] = bfhi(xr.y);
                if (s != 0) {
                    float4 a = __ldcg(reinterpret_cast<const float4*>(&g_acc[s - 1][0][0]) + tid);
#pragma unroll
                    for (int i = 1; i < NREP; i++) {
                        const float4 a2 = __ldcg(reinterpret_cast<const float4*>(&g_acc[s - 1][i][0]) + tid);
                        a.x += a2.x; a.y += a2.y; a.z += a2.z; a.w += a2.w;
                    }
                    a.x = bf16r(a.x); a.y = bf16r(a.y); a.z = bf16r(a.z); a.w = bf16r(a.w);
                    if (s == 2) {
                        const uint2 br = *reinterpret_cast<const uint2*>(b2s + tid * 4);
                        a.x = bf16r(a.x + bflo(br.x)); a.y = bf16r(a.y + bfhi(br.x));
                        a.z = bf16r(a.z + bflo(br.y)); a.w = bf16r(a.w + bfhi(br.y));
                    }
                    v[0] = bf16r(v[0] + a.x); v[1] = bf16r(v[1] + a.y); v[2] = bf16r(v[2] + a.z); v[3] = bf16r(v[3] + a.w);
                    *reinterpret_cast<uint2*>(xs + tid * 4) = make_uint2(pack_bf16(v[0], v[1]), pack_bf16(v[2], v[3]));
                }
            }
            if (s == 2 && b == 0) {
                for (int e = tid; e < NREP * D_MODEL; e += NT) (&g_acc[0][0][0])[e] = 0.f;
            }
#pragma unroll 1
            for (int rep = 0; rep <= (s & 1); rep++) {
                float mean = 0.25f * ((v[0] + v[1]) + (v[2] + v[3]));
                float m2 = (v[0] - mean) * (v[0] - mean) + (v[1] - mean) * (v[1] - mean) +
                           (v[2] - mean) * (v[2] - mean) + (v[3] - mean) * (v[3] - mean);
                float hn = 2.f;
#pragma unroll
                for (int o = 1; o < 32; o <<= 1) {
                    const float mo = __shfl_xor_sync(0xffffffffu, mean, o);
                    const float qo = __shfl_xor_sync(0xffffffffu, m2, o);
                    const float d = mo - mean;
                    m2 = m2 + qo + d * d * hn;
                    mean = 0.5f * (mean + mo);
                    hn *= 2.f;
                }
                float* rd = red + rep * 12;
                if (lane == 0 && w < 5) { rd[2 * w] = mean; rd[2 * w + 1] = m2; }
                __syncthreads();
                float gm = 0.f, gq = 0.f;
#pragma unroll
                for (int i = 0; i < 5; i++) { gm += rd[2 * i]; gq += rd[2 * i + 1]; }
                gm *= 0.2f;
#pragma unroll
                for (int i = 0; i < 5; i++) { const float d = rd[2 * i] - gm; gq += 128.f * d * d; }
                const float mb = bf16r(gm);
                const float den = bf16r(sqrtf(bf16r(bf16r(gq * (1.0f / D_MODEL)) + 1e-5f)));
#pragma unroll
                for (int i = 0; i < 4; i++) v[i] = bf16r(__fdividef(bf16r(v[i] - mb), den));
            }
            if (tid < D_MODEL / 4)
                *reinterpret_cast<uint2*>(xn + tid * 4) = make_uint2(pack_bf16(v[0], v[1]), pack_bf16(v[2], v[3]));
        }
        if (s == 1) cp_async_wait_all();
        __syncthreads();
        float* acc = &g_acc[s][b & (NREP - 1)][0];

        if (!(s & 1)) {
            const int pass = s >> 1;
            mbar_wait(bar_stage, 0);
            {
                float cq[4][4];
#pragma unroll
                for (int i = 0; i < 4; i++) { cq[i][0] = cq[i][1] = cq[i][2] = cq[i][3] = 0.f; }
#pragma unroll
                for (int k5 = 0; k5 < 5; k5++) {
                    const int ks = w * 5 + k5;
                    const uint32_t b0 = *reinterpret_cast<const uint32_t*>(xn + ks * 16 + 2 * t);
                    const uint32_t b1 = *reinterpret_cast<const uint32_t*>(xn + ks * 16 + 2 * t + 8);
                    const int krow = ks * 16 + (lane & 7) + ((lane >> 4) & 1) * 8;
#pragma unroll
                    for (int mt = 0; mt < 4; mt++) {
                        uint32_t a[4];
                        ldmatrix4t(a, sbase + OFF_STAGE + krow * 128 + (((2 * mt + ((lane >> 3) & 1)) ^ (lane & 7)) << 4));
                        mma16816(cq[mt], a[0], a[1], a[2], a[3], b0, b1);
                    }
                }
                if (t == 0) {
#pragma unroll
                    for (int mt = 0; mt < 4; mt++) { oscr[w * 64 + mt * 16 + g] = cq[mt][0]; oscr[w * 64 + mt * 16 + 8 + g] = cq[mt][2]; }
                }
            }
            __syncthreads();
            if (s == 0) asm volatile("barrier.cluster.wait.aligned;" ::: "memory");
            if (tid < 32) {
                float s0 = 0.f, s1 = 0.f;
#pragma unroll
                for (int i = 0; i < 8; i++) { const float2 v2 = *reinterpret_cast<const float2*>(oscr + i * 64 + 2 * tid); s0 += v2.x; s1 += v2.y; }
                const uint32_t qp = pack_bf16(s0, s1);
                *reinterpret_cast<uint32_t*>(qs + r * 64 + 2 * tid) = qp;
                st_async_b32(mapa(sbase + OFF_Q + (r * 64 + 2 * tid) * 2, r ^ 1), qp, mapa(sbase + OFF_XBAR, r ^ 1));
                if (tid == 0) { mbar_expect_tx(sbase + OFF_XBAR, 128); mbar_expect_tx(sbase + OFF_XBAR + 8, 256); }
            }
            const uint32_t vland = sbase + OFF_STAGE + w * (VL * 4096);
#pragma unroll 1
            for (int it = 0; it < VL * 8; it++) {
                const int idx = it * 32 + lane;
                const int row = idx >> 4, ch = idx & 15;
                cp_async16_hint(vland + row * 256 + ((ch ^ (row & 7)) << 4), P.vc + kv_off + row * DH + ch * 8, pol_first);
            }
            cp_async_commit();
            if (s == 0) {
                const bf16* kp = P.kc + kv_off + (g * DH + t * 8);
#pragma unroll
                for (int i = 0; i < KREG_TILES; i++)
#pragma unroll
                    for (int hh = 0; hh < 2; hh++)
#pragma unroll
                        for (int j = 0; j < 4; j++)
                            ldg128_hint(kreg[i][hh][j], kp + (i * 16 + hh * 8) * DH + j * 32, pol_first);
            }
            __syncthreads();
            mbar_wait(sbase + OFF_XBAR, pass);

            float sc[8][2];
            {
                float cacc[KREG_TILES][4];
#pragma unroll
                for (int i = 0; i < KREG_TILES; i++) { cacc[i][0] = cacc[i][1] = cacc[i][2] = cacc[i][3] = 0.f; }
#pragma unroll
                for (int j = 0; j < 4; j++) {
                    const uint4 qv = *reinterpret_cast<const uint4*>(qs + j * 32 + t * 8);
#pragma unroll
                    for (int i = 0; i < KREG_TILES; i++) {
                        mma16816(cacc[i], kreg[i][0][j][0], kreg[i][1][j][0], kreg[i][0][j][1], kreg[i][1][j][1], qv.x, qv.y);
                        mma16816(cacc[i], kreg[i][0][j][2], kreg[i][1][j][2], kreg[i][0][j][3], kreg[i][1][j][3], qv.z, qv.w);
                    }
                }
#pragma unroll
                for (int i = 0; i < KREG_TILES; i++) { sc[i][0] = cacc[i][0]; sc[i][1] = cacc[i][2]; }
            }
            {
                if (s == 0) {
                    if (lane == 0) bulk_prefetch_l2(P.vc + kv_off + VL * 16 * DH, (8 - VL) * 4096);
                    cp_async_wait_group<1>();
                    __syncwarp();
                }
                float cacc[KSM_TILES][4];
#pragma unroll
                for (int tt = 0; tt < KSM_TILES; tt++) { cacc[tt][0] = cacc[tt][1] = cacc[tt][2] = cacc[tt][3] = 0.f; }
                const int row0 = (lane & 7) + ((lane >> 3) & 1) * 8;
#pragma unroll 4
                for (int ks = 0; ks < 8; ks++) {
                    const uint32_t b0 = *reinterpret_cast<const uint32_t*>(qs + ks * 16 + 2 * t);
                    const uint32_t b1 = *reinterpret_cast<const uint32_t*>(qs + ks * 16 + 2 * t + 8);
                    const int ch = 2 * ks + (lane >> 4);
                    const uint32_t ad = kb + row0 * 256 + ((ch ^ (lane & 7)) << 4);
#pragma unroll
                    for (int tt = 0; tt < KSM_TILES; tt++) {
                        uint32_t a[4];
                        ldmatrix4(a, ad + tt * 4096);
                        mma16816(cacc[tt], a[0], a[1], a[2], a[3], b0, b1);
                    }
                }
#pragma unroll
                for (int tt = 0; tt < KSM_TILES; tt++) { sc[KREG_TILES + tt][0] = cacc[tt][0]; sc[KREG_TILES + tt][1] = cacc[tt][2]; }
            }
            bf16* pw = reinterpret_cast<bf16*>(sm + OFF_P + w * 256);
            {
                float s4[4];
#pragma unroll
                for (int q2 = 0; q2 < 4; q2++) {
                    const int i = q2 >> 1, k2 = q2 & 1;
                    const float v01 = (t & 1) ? sc[2 + i][k2] : sc[i][k2];
                    const float v23 = (t & 1) ? sc[6 + i][k2] : sc[4 + i][k2];
                    s4[q2] = (t & 2) ? v23 : v01;
                }
                float mx = -INFINITY;
#pragma unroll
                for (int q2 = 0; q2 < 4; q2++) {
                    s4[q2] = bf16r(bf16r(s4[q2]) * 0.08838834764831845f);
                    mx = fmaxf(mx, s4[q2]);
                }
#pragma unroll
                for (int o = 1; o < 32; o <<= 1) mx = fmaxf(mx, __shfl_xor_sync(0xffffffffu, mx, o));
                float l = 0.f;
#pragma unroll
                for (int q2 = 0; q2 < 4; q2++) {
                    const bf16 pb = __float2bfloat16_rn(ex2((s4[q2] - mx) * LOG2E));
                    l += __bfloat162float(pb);
                    pw[(2 * t + (q2 >> 1)) * 16 + (q2 & 1) * 8 + g] = pb;
                }
                l = warp_sum(l);
                if (lane == 0) { stat[2 * w] = mx; stat[2 * w + 1] = l; }
            }
            __syncthreads();
            float m_cta = stat[0];
#pragma unroll
            for (int i = 1; i < 8; i++) m_cta = fmaxf(m_cta, stat[2 * i]);
            const float wfac = ex2((stat[2 * w] - m_cta) * LOG2E);
            if (tid == 0) {
                float l_cta = 0.f;
#pragma unroll
                for (int i = 0; i < 8; i++) l_cta += stat[2 * i + 1] * ex2((stat[2 * i] - m_cta) * LOG2E);
                asm volatile("st.relaxed.gpu.global.v4.u32 [%0], {%1,%2,%3,%4};" :: "l"(&g_ml[pass][b]),
                             "r"(__float_as_uint(m_cta)), "r"(__float_as_uint(l_cta)), "r"(epoch * 2 + pass + 1), "r"(0u) : "memory");
            }

            {
                const bf16* vbase = P.vc + kv_off + (4 * t) * DH + g * 8;
                float* ow = oscr + w * 128;
                constexpr int NK = 8 - VL;
                static_assert(NK % NVB == 0, "NVB");
                uint32_t vbuf[NVB][4][4];
#pragma unroll
                for (int u = 0; u < NVB - 1; u++)
#pragma unroll
                    for (int i = 0; i < 4; i++) ldg128_hint(vbuf[u][i], vbase + ((VL + u) * 16 + i) * DH, pol_norm);
                cp_async_wait_all();
                __syncwarp();
#pragma unroll 4
                for (int mt = 0; mt < 8; mt++) {
                    float cl[4] = {0.f, 0.f, 0.f, 0.f};
#pragma unroll
                    for (int kt = 0; kt < VL; kt++) {
                        const uint32_t b0 = *reinterpret_cast<const uint32_t*>(pw + kt * 16 + 2 * t);
                        const uint32_t b1 = *reinterpret_cast<const uint32_t*>(pw + kt * 16 + 2 * t + 8);
                        const int row = kt * 16 + (lane & 7) + ((lane >> 4) & 1) * 8;
                        uint32_t a[4];
                        ldmatrix4t(a, vland + row * 256 + (((2 * mt + ((lane >> 3) & 1)) ^ (lane & 7)) << 4));
                        mma16816(cl, a[0], a[1], a[2], a[3], b0, b1);
                    }
                    if (t == 0) { ow[mt * 16 + g] = cl[0] * wfac; ow[mt * 16 + 8 + g] = cl[2] * wfac; }
                }
                __syncwarp();
                if (w != 7) asm volatile("bar.arrive 1, 256;" ::: "memory");
                float oacc[4][4];
#pragma unroll
                for (int i = 0; i < 4; i++) { oacc[i][0] = oacc[i][1] = oacc[i][2] = oacc[i][3] = 0.f; }
#pragma unroll 1
                for (int hf = 0; hf < 2; hf++) {
#pragma unroll 1
                    for (int k0 = 0; k0 < NK; k0 += NVB) {
                        if (w == 7 && hf == 1 && k0 == 2) {
                            asm volatile("bar.sync 1, 256;" ::: "memory");
                            if (lane == 0) {
                                mbar_expect_tx(bar_stage, 81920);
#pragma unroll 1
                                for (int i = 0; i < 10; i++) tma_2d_hint(sbase + OFF_STAGE + i * 8192, &tm_wo, i * 64, h * DH + r * 64, bar_stage, pol_first);
                            }
                            __syncwarp();
                        }
#pragma unroll
                        for (int u = 0; u < NVB; u++) {
                            const int kt = k0 + u;
                            int nk = kt + NVB - 1, nh = hf;
                            if (nk >= NK) { nk -= NK; nh = hf + 1; }
                            if (nh < 2) {
                                const bf16* vp = vbase + (VL + nk) * 16 * DH + nh * 64;
#pragma unroll
                                for (int i = 0; i < 4; i++) ldg128_hint(vbuf[(u + NVB - 1) % NVB][i], vp + i * DH, pol_norm);
                            }
                            const uint2 pb = *reinterpret_cast<const uint2*>(pw + (VL + kt) * 16 + 4 * t);
#pragma unroll
                            for (int e = 0; e < 4; e++)
                                mma16816(oacc[e], __byte_perm(vbuf[u][0][e], vbuf[u][1][e], 0x5410), __byte_perm(vbuf[u][0][e], vbuf[u][1][e], 0x7632),
                                         __byte_perm(vbuf[u][2][e], vbuf[u][3][e], 0x5410), __byte_perm(vbuf[u][2][e], vbuf[u][3][e], 0x7632), pb.x, pb.y);
                        }
                    }
                    if (t == 0) {
                        float* o2 = ow + hf * 64 + g * 8;
                        float4 u0 = *reinterpret_cast<float4*>(o2), u1 = *reinterpret_cast<float4*>(o2 + 4);
                        u0.x += oacc[0][0] * wfac; u0.y += oacc[0][2] * wfac; u0.z += oacc[1][0] * wfac; u0.w += oacc[1][2] * wfac;
                        u1.x += oacc[2][0] * wfac; u1.y += oacc[2][2] * wfac; u1.z += oacc[3][0] * wfac; u1.w += oacc[3][2] * wfac;
                        *reinterpret_cast<float4*>(o2) = u0;
                        *reinterpret_cast<float4*>(o2 + 4) = u1;
                    }
#pragma unroll
                    for (int i = 0; i < 4; i++) { oacc[i][0] = oacc[i][1] = oacc[i][2] = oacc[i][3] = 0.f; }
                }
            }
            if (s == 0 && b < MLP_CTAS) {
#pragma unroll 1
                for (int idx = tid; idx < 2 * D_MODEL; idx += NT) {
                    const int row = idx >> 1, hf = idx & 1;
                    cp_async16_hint(sbase + OFF_W1 + row * 32 + hf * 16, P.w1 + (size_t)row * FF + b * MLP_UNITS + hf * 8, pol_first);
                    const int r2 = idx / 80, ch = idx - r2 * 80;
                    cp_async16_hint(sbase + OFF_W2 + r2 * 1280 + ((ch ^ (r2 & 7)) << 4), P.w2 + (size_t)(b * MLP_UNITS) * D_MODEL + idx * 8, pol_first);
                }
                cp_async_commit();
            }
            __syncthreads();
            if (tid < 128) {
                uint4 rec[4];
                {
                    unsigned it = 0;
                    const unsigned tag = epoch * 2 + pass + 1;
                    while (true) {
#pragma unroll
                        for (int i = 0; i < 4; i++)
                            asm volatile("ld.relaxed.gpu.global.v4.u32 {%0,%1,%2,%3}, [%4];"
                                         : "=r"(rec[i].x), "=r"(rec[i].y), "=r"(rec[i].z), "=r"(rec[i].w)
                                         : "l"(&g_ml[pass][(b & ~3) + i]) : "memory");
                        if (rec[0].z == tag && rec[1].z == tag && rec[2].z == tag && rec[3].z == tag) break;
                        if (++it > SPIN_LIMIT) __trap();
                    }
                }
                const float M = fmaxf(fmaxf(__uint_as_float(rec[0].x), __uint_as_float(rec[1].x)),
                                      fmaxf(__uint_as_float(rec[2].x), __uint_as_float(rec[3].x)));
                float L = 0.f;
#pragma unroll
                for (int i = 0; i < 4; i++) L += __uint_as_float(rec[i].y) * ex2((__uint_as_float(rec[i].x) - M) * LOG2E);
                const float scale = __fdividef(ex2((m_cta - M) * LOG2E), L);
                float sum = 0.f;
#pragma unroll
                for (int i = 0; i < 8; i++) sum += oscr[i * 128 + tid];
                if ((tid >> 6) == r) oex[r * 64 + (tid & 63)] = sum * scale;
                else st_async_b32(mapa(sbase + OFF_OEX + (r * 64 + (tid & 63)) * 4, r ^ 1), __float_as_uint(sum * scale), mapa(sbase + OFF_XBAR + 8, r ^ 1));
            }
            __syncthreads();
            if (tid < 64) {
                mbar_wait(sbase + OFF_XBAR + 8, pass);
                const float o = oex[tid] + oex[64 + tid];
                const bf16 hi = __float2bfloat16_rn(o);
                hs[32 + tid] = hi;
                hs[96 + tid] = __float2bfloat16_rn(o - __bfloat162float(hi));
            }
            mbar_wait(bar_stage, 1);
            __syncthreads();
            {
                float co[5][4];
#pragma unroll
                for (int i = 0; i < 5; i++) { co[i][0] = co[i][1] = co[i][2] = co[i][3] = 0.f; }
#pragma unroll 1
                for (int ks = 0; ks < 4; ks++) {
                    uint32_t b0 = 0, b1 = 0;
                    if (g < 2) {
                        b0 = *reinterpret_cast<const uint32_t*>(hs + 32 + g * 64 + ks * 16 + 2 * t);
                        b1 = *reinterpret_cast<const uint32_t*>(hs + 32 + g * 64 + ks * 16 + 2 * t + 8);
                    }
                    const int krow = ks * 16 + (lane & 7) + ((lane >> 4) & 1) * 8;
#pragma unroll
                    for (int i = 0; i < 5; i++) {
                        const int ch = 2 * (w * 5 + i) + ((lane >> 3) & 1);
                        uint32_t a[4];
                        ldmatrix4t(a, sbase + OFF_STAGE + (ch >> 3) * 8192 + krow * 128 + (((ch ^ lane) & 7) << 4));
                        mma16816(co[i], a[0], a[1], a[2], a[3], b0, b1);
                    }
                }
                if (t == 0) {
#pragma unroll
                    for (int i = 0; i < 5; i++) {
                        oscr[(w * 5 + i) * 16 + g] = co[i][0] + co[i][1];
                        oscr[(w * 5 + i) * 16 + 8 + g] = co[i][2] + co[i][3];
                    }
                }
                __syncwarp();
                if (lane < 20) {
                    const float4 v4 = *reinterpret_cast<const float4*>(oscr + w * 80 + lane * 4);
                    red_add_v4(acc + w * 80 + lane * 4, v4.x, v4.y, v4.z, v4.w);
                }
            }
            if (s == 0) {
                __syncthreads();
                if (tid == 224) {
                    mbar_expect_tx(bar_stage, 81920);
#pragma unroll 1
                    for (int i = 0; i < 5; i++) tma_2d_hint(sbase + OFF_STAGE + i * 16384, &tm_wq, h * DH + r * 64, i * 128, bar_stage, pol_first);
                }
            }
        } else if (b < MLP_CTAS) {
            {
                float ch4[4] = {0.f, 0.f, 0.f, 0.f};
#pragma unroll
                for (int k5 = 0; k5 < 5; k5++) {
                    const int ks = w * 5 + k5;
                    const uint32_t b0 = *reinterpret_cast<const uint32_t*>(xn + ks * 16 + 2 * t);
                    const uint32_t b1 = *reinterpret_cast<const uint32_t*>(xn + ks * 16 + 2 * t + 8);
                    const int krow = ks * 16 + (lane & 7) + ((lane >> 4) & 1) * 8;
                    uint32_t a[4];
                    ldmatrix4t(a, sbase + OFF_W1 + krow * 32 + ((lane >> 3) & 1) * 16);
                    mma16816(ch4, a[0], a[1], a[2], a[3], b0, b1);
                }
                if (t == 0) { oscr[w * 16 + g] = ch4[0]; oscr[w * 16 + 8 + g] = ch4[2]; }
            }
            __syncthreads();
            if (tid < 16) {
                float sum = 0.f;
#pragma unroll
                for (int i = 0; i < 8; i++) sum += oscr[i * 16 + tid];
                const float u = bf16r(bf16r(sum) + __bfloat162float(hs[16 + tid]));
                const float inner = 0.7978845608028654f * (u + 0.044715f * u * u * u);
                const float th = 1.0f - __fdividef(2.0f, ex2(inner * (2.0f * LOG2E)) + 1.0f);
                hs[tid] = __float2bfloat16_rn(0.5f * u * (1.0f + th));
            }
            __syncthreads();
            {
                const uint32_t b0 = *reinterpret_cast<const uint32_t*>(hs + 2 * t);
                const uint32_t b1 = *reinterpret_cast<const uint32_t*>(hs + 2 * t + 8);
                const int krow = (lane & 7) + ((lane >> 4) & 1) * 8;
#pragma unroll
                for (int i = 0; i < 5; i++) {
                    const int ch = 2 * (w * 5 + i) + ((lane >> 3) & 1);
                    uint32_t a[4];
                    float co[4] = {0.f, 0.f, 0.f, 0.f};
                    ldmatrix4t(a, sbase + OFF_W2 + krow * 1280 + ((ch ^ (lane & 7)) << 4));
                    mma16816(co, a[0], a[1], a[2], a[3], b0, b1);
                    if (t == 0) {
                        oscr[256 + (w * 5 + i) * 16 + g] = co[0];
                        oscr[256 + (w * 5 + i) * 16 + 8 + g] = co[2];
                    }
                }
                __syncwarp();
                if (lane < 20) {
                    const float4 v4 = *reinterpret_cast<const float4*>(oscr + 256 + w * 80 + lane * 4);
                    red_add_v4(acc + w * 80 + lane * 4, v4.x, v4.y, v4.z, v4.w);
                }
            }
        }
        if (s < 3) grid_barrier(base + NCTA * (s + 1));
    }
    __syncthreads();
    if (tid == 0) {
        unsigned old;
        asm volatile("atom.acq_rel.gpu.global.add.u32 %0, [%1], 1;" : "=r"(old) : "l"(&g_ctr) : "memory");
        s_flag[1] = (old == base + 4 * NCTA - 1) ? 1u : 0u;
    }
    __syncthreads();
    if (s_flag[1]) {
        for (int e = tid; e < D_MODEL; e += NT) {
            float a = 0.f;
#pragma unroll
            for (int i = 0; i < NREP; i++) a += __ldcg(&g_acc[3][i][e]);
            const float o = bf16r(bf16r(a) + __bfloat162float(b2s[e]));
            P.out[e] = __float2bfloat16_rn(__bfloat162float(xs[e]) + o);
        }
    }
}

}

extern "C" void kernel_launch(void* const* d_in, const int* in_sizes, int n_in,
                              void* d_out, int out_size) {
    Params P;
    P.x = (const bf16*)d_in[0];
    P.kc = (const bf16*)d_in[1];
    P.vc = (const bf16*)d_in[2];
    P.wq = (const bf16*)d_in[3];
    P.wo = (const bf16*)d_in[4];
    P.w1 = (const bf16*)d_in[6];
    P.b1 = (const bf16*)d_in[7];
    P.w2 = (const bf16*)d_in[8];
    P.b2 = (const bf16*)d_in[9];
    P.out = (bf16*)d_out;

    cudaFuncSetAttribute(fused_kernel, cudaFuncAttributeMaxDynamicSharedMemorySize, SMEM_BYTES);

    typedef CUresult (*EncodeFn)(CUtensorMap*, CUtensorMapDataType, cuuint32_t, void*, const cuuint64_t*, const cuuint64_t*,
                                 const cuuint32_t*, const cuuint32_t*, CUtensorMapInterleave, CUtensorMapSwizzle,
                                 CUtensorMapL2promotion, CUtensorMapFloatOOBfill);
    void* fn = nullptr;
    cudaDriverEntryPointQueryResult qres;
    cudaGetDriverEntryPoint("cuTensorMapEncodeTiled", &fn, cudaEnableDefault, &qres);
    EncodeFn encode = (EncodeFn)fn;
    CUtensorMap tm_wq, tm_wo;
    {
        cuuint64_t dims[2] = {(cuuint64_t)(NHEAD * DH), (cuuint64_t)D_MODEL};
        cuuint64_t strides[1] = {(cuuint64_t)(NHEAD * DH * 2)};
        cuuint32_t box[2] = {64, 128};
        cuuint32_t es[2] = {1, 1};
        encode(&tm_wq, CU_TENSOR_MAP_DATA_TYPE_BFLOAT16, 2, (void*)P.wq, dims, strides, box, es, CU_TENSOR_MAP_INTERLEAVE_NONE,
               CU_TENSOR_MAP_SWIZZLE_128B, CU_TENSOR_MAP_L2_PROMOTION_NONE, CU_TENSOR_MAP_FLOAT_OOB_FILL_NONE);
    }
    {
        cuuint64_t dims[2] = {(cuuint64_t)D_MODEL, (cuuint64_t)(NHEAD * DH)};
        cuuint64_t strides[1] = {(cuuint64_t)(D_MODEL * 2)};
        cuuint32_t box[2] = {64, 64};
        cuuint32_t es[2] = {1, 1};
        encode(&tm_wo, CU_TENSOR_MAP_DATA_TYPE_BFLOAT16, 2, (void*)P.wo, dims, strides, box, es, CU_TENSOR_MAP_INTERLEAVE_NONE,
               CU_TENSOR_MAP_SWIZZLE_128B, CU_TENSOR_MAP_L2_PROMOTION_NONE, CU_TENSOR_MAP_FLOAT_OOB_FILL_NONE);
    }

    cudaLaunchConfig_t cfg = {};
    cfg.gridDim = dim3(NCTA);
    cfg.blockDim = dim3(NT);
    cfg.dynamicSmemBytes = SMEM_BYTES;
    cfg.stream = cudaStreamPerThread;
    cudaLaunchAttribute at[2];
    at[0].id = cudaLaunchAttributeClusterDimension;
    at[0].val.clusterDim.x = 2; at[0].val.clusterDim.y = 1; at[0].val.clusterDim.z = 1;
    at[1].id = cudaLaunchAttributeCooperative;
    at[1].val.cooperative = 1;
    cfg.attrs = at;
    cfg.numAttrs = 2;
    cudaLaunchKernelEx(&cfg, fused_kernel, P, tm_wq, tm_wo);
}
```
